```python
import torch

def _softmax(x, axis=-1):
    return torch.softmax(x, dim=axis)
def _gelu(x):
    return torch.nn.functional.gelu(x, approximate="tanh")
def _silu(x):
    return torch.nn.functional.silu(x)
def _sigmoid(x):
    return torch.sigmoid(x)
def _layernorm(x, axis=-1, eps=1e-5):
    m = x.mean(dim=axis, keepdim=True)
    v = x.var(dim=axis, keepdim=True, unbiased=False)
    return (x - m) / torch.sqrt(v + eps)
def _scatter_add(tgt, idx, src, axis=0):
    return tgt.clone().index_add_(axis, idx, src)
def _segment_sum(src, seg, n):
    out = torch.zeros((n,) + src.shape[1:], dtype=src.dtype)
    return out.index_add_(0, seg, src)
def _pad(x, pw):
    flat = tuple(v for pair in reversed(pw) for v in pair)
    return torch.nn.functional.pad(x, flat)

kernel_name = 'parallel_sum__spectral_fnet__geglu_ffn__prompt'

def setup_inputs():

    _w = (lambda a: (lambda t: t.to(torch.bfloat16) if t.is_floating_point() else t)(torch.as_tensor(a)))
    def _A_setup():
        B, S, D = 1, 2048, 512
        ns = torch.arange(S)[:, None] * torch.arange(S)[None, :]
        nd = torch.arange(D)[:, None] * torch.arange(D)[None, :]
        Ws_re = torch.cos(-2.0 * torch.pi * ns / S).to(float)
        Ws_im = torch.sin(-2.0 * torch.pi * ns / S).to(float)
        Wd_re = torch.cos(-2.0 * torch.pi * nd / D).to(float)
        Wd_im = torch.sin(-2.0 * torch.pi * nd / D).to(float)
        return {
            "x": _w((lambda *s: torch.randn(*s, dtype=torch.bfloat16) * 0.05)(B, S, D)),
            "dft_seq_re": _w(Ws_re),
            "dft_seq_im": _w(Ws_im),
            "dft_hid_re": _w(Wd_re),
            "dft_hid_im": _w(Wd_im),
        }
    _A_in = _A_setup()

    def _B_setup():
        B, S, D, F = 1, 2048, 512, 1792
        return {
            "x": _w((lambda *s: torch.randn(*s, dtype=torch.bfloat16) * 0.05)(B, S, D)),
            "w_gate": _w((lambda *s: torch.randn(*s, dtype=torch.bfloat16) * 0.2)(D, F)),
            "w_up": _w((lambda *s: torch.randn(*s, dtype=torch.bfloat16) * 0.2)(D, F)),
            "w_down": _w((lambda *s: torch.randn(*s, dtype=torch.bfloat16) * 0.2)(F, D)),
        }
    _B_in = _B_setup()

    return {
        "A_x": _A_in["x"],
        "A_dft_seq_re": _A_in["dft_seq_re"],
        "A_dft_seq_im": _A_in["dft_seq_im"],
        "A_dft_hid_re": _A_in["dft_hid_re"],
        "A_dft_hid_im": _A_in["dft_hid_im"],
        "B_x": _B_in["x"],
        "B_w_gate": _B_in["w_gate"],
        "B_w_up": _B_in["w_up"],
        "B_w_down": _B_in["w_down"],
    }

def reference(A_x, A_dft_seq_re, A_dft_seq_im, A_dft_hid_re, A_dft_hid_im, B_x, B_w_gate, B_w_up, B_w_down):
    def _A_ref(x, dft_seq_re, dft_seq_im, dft_hid_re, dft_hid_im):
        a = torch.einsum("bsd,ed->bse", x, dft_hid_re)
        b = torch.einsum("bsd,ed->bse", x, dft_hid_im)
        y = torch.einsum("ts,bse->bte", dft_seq_re, a) - torch.einsum("ts,bse->bte", dft_seq_im, b)
        return y

    def _B_ref(x, w_gate, w_up, w_down):
        return (_gelu(x @ w_gate) * (x @ w_up)) @ w_down

    x = A_x
    xn = _layernorm(x, axis=-1)
    return x + _A_ref(xn, A_dft_seq_re, A_dft_seq_im, A_dft_hid_re, A_dft_hid_im) + _B_ref(xn, B_w_gate, B_w_up, B_w_down)
```

```cpp
#include <cuda_runtime.h>
#include <cuda.h>
#include <cuda_bf16.h>
#include <stdint.h>

namespace {

constexpr int S = 2048, D = 512, F = 1792;
constexpr int NCTA = 128, NHELP = 4, NTHREADS = 384;
constexpr int SLOT = 16384;
constexpr int SMEM_STAT = 14 * SLOT;
constexpr int SMEM_CS = SMEM_STAT + 1024;
constexpr int SMEM_BAR = SMEM_CS + 1024;
constexpr int SMEM_TOTAL = SMEM_BAR + 1024;
constexpr int MB_EMPTY = 32, MB_RFULL = 64, MB_REMPTY = 112, MB_EARLY = 160, MB_AB = 168, MB_H = 176, MB_X = 184, MB_CS = 248;
constexpr int SM_PROG = 288, SM_TAG = 292;
constexpr int BAR_ORDER = 1, BAR_TAIL = 3, BAR_PUB = 4;
#define PF2_DIST 6
#define C_POLICY EVICT_FIRST
#define W_POLICY EVICT_FIRST
constexpr int SPIN_LIMIT = 1 << 18;

__device__ __nv_bfloat16 g_ab[2 * S * D];
__device__ __nv_bfloat16 g_h[S * F];
__device__ uint4 g_part[NCTA * 3 * 4 * 256];
__device__ uint2 g_stat[S];
__device__ uint4 g_cs[36 * 32];
__device__ unsigned g_cnt[17 * 32];
__device__ unsigned g_epoch[NCTA + NHELP];
#define PROF(role, i) do { } while (0)
#define PROFC(i) do { if ((threadIdx.x & 127) == 0) PROF(threadIdx.x >> 7, i); } while (0)

struct Maps {
  CUtensorMap cr, ci, h, hr, hi, wg, wu, wd, ab, x, out;
};
struct Ptrs {
  const __nv_bfloat16 *x, *hr, *hi;
  __nv_bfloat16 *ab, *h;
  uint4 *part, *cs;
  uint2* stat;
  unsigned *cnt, *epoch;
  uint32_t zero;
};

__device__ __forceinline__ uint32_t smem_u32(const void* p) { return (uint32_t)__cvta_generic_to_shared(p); }
__device__ __forceinline__ void mbar_init(uint32_t bar, uint32_t cnt) {
  asm volatile("mbarrier.init.shared::cta.b64 [%0], %1;" :: "r"(bar), "r"(cnt));
}
__device__ __forceinline__ void mbar_expect_tx(uint32_t bar, uint32_t bytes) {
  asm volatile("mbarrier.arrive.expect_tx.shared::cta.b64 _, [%0], %1;" :: "r"(bar), "r"(bytes) : "memory");
}
__device__ __forceinline__ void mbar_arrive(uint32_t bar) {
  asm volatile("mbarrier.arrive.shared::cta.b64 _, [%0];" :: "r"(bar) : "memory");
}
__device__ __forceinline__ void mbar_arrive_cluster(uint32_t cluster_addr) {
  asm volatile("mbarrier.arrive.shared::cluster.b64 _, [%0];" :: "r"(cluster_addr) : "memory");
}
__device__ __forceinline__ uint32_t mapa(uint32_t addr, uint32_t cta) {
  uint32_t r; asm("mapa.shared::cluster.u32 %0, %1, %2;" : "=r"(r) : "r"(addr), "r"(cta)); return r;
}
__device__ __forceinline__ void mbar_wait(uint32_t bar, uint32_t parity) {
  asm volatile("{ .reg .pred p; .reg .u32 n;\n"
               "mbarrier.try_wait.parity.shared::cta.b64 p, [%0], %1;\n"
               "@p bra DONE;\n"
               "mov.u32 n, 0;\n"
               "LOOP:\n"
               "mbarrier.try_wait.parity.shared::cta.b64 p, [%0], %1;\n"
               "@p bra DONE;\n"
               "add.u32 n, n, 1;\n"
               "setp.lt.u32 p, n, %2;\n"
               "@p bra LOOP;\n"
               "DONE: }" :: "r"(bar), "r"(parity), "n"(SPIN_LIMIT) : "memory");
}
constexpr uint64_t EVICT_NORMAL = 0x1000000000000000ull, EVICT_FIRST = 0x12F0000000000000ull;
__device__ __forceinline__ void tma_2d(uint32_t dst, const CUtensorMap* m, int c0, int c1, uint32_t bar, uint64_t pol = EVICT_NORMAL) {
  asm volatile("cp.async.bulk.tensor.2d.shared::cluster.global.mbarrier::complete_tx::bytes.L2::cache_hint [%0], [%1, {%3, %4}], [%2], %5;"
               :: "r"(dst), "l"(m), "r"(bar), "r"(c0), "r"(c1), "l"(pol) : "memory");
}
__device__ __forceinline__ void tma_2d_mc(uint32_t dst, const CUtensorMap* m, int c0, int c1, uint32_t bar, uint64_t pol = EVICT_NORMAL) {
  asm volatile("cp.async.bulk.tensor.2d.shared::cluster.global.mbarrier::complete_tx::bytes.multicast::cluster.L2::cache_hint [%0], [%1, {%3, %4}], [%2], %5, %6;"
               :: "r"(dst), "l"(m), "r"(bar), "r"(c0), "r"(c1), "h"((uint16_t)3), "l"(pol) : "memory");
}
__device__ __forceinline__ void tma_5d_mc(uint32_t dst, const CUtensorMap* m, int c0, int c4, uint32_t bar, uint64_t pol = EVICT_NORMAL) {
  asm volatile("cp.async.bulk.tensor.5d.shared::cluster.global.mbarrier::complete_tx::bytes.multicast::cluster.L2::cache_hint [%0], [%1, {%3, %5, %5, %5, %4}], [%2], %6, %7;"
               :: "r"(dst), "l"(m), "r"(bar), "r"(c0), "r"(c4), "r"(0), "h"((uint16_t)3), "l"(pol) : "memory");
}
__device__ __forceinline__ void tma_5d(uint32_t dst, const CUtensorMap* m, int c0, int c4, uint32_t bar) {
  asm volatile("cp.async.bulk.tensor.5d.shared::cluster.global.mbarrier::complete_tx::bytes [%0], [%1, {%3, %5, %5, %5, %4}], [%2];"
               :: "r"(dst), "l"(m), "r"(bar), "r"(c0), "r"(c4), "r"(0) : "memory");
}
__device__ __forceinline__ void prefetch_bulk(const void* p, uint32_t bytes) {
  asm volatile("cp.async.bulk.prefetch.L2.global [%0], %1;" :: "l"(p), "r"(bytes) : "memory");
}
__device__ __forceinline__ void tma_store_2d(const CUtensorMap* m, uint32_t src, int c0, int c1) {
  asm volatile("cp.async.bulk.tensor.2d.global.shared::cta.bulk_group [%0, {%2, %3}], [%1];"
               :: "l"(m), "r"(src), "r"(c0), "r"(c1) : "memory");
}
__device__ __forceinline__ void prefetch_2d(const CUtensorMap* m, int c0, int c1) {
  asm volatile("cp.async.bulk.prefetch.tensor.2d.L2.global [%0, {%1, %2}];" :: "l"(m), "r"(c0), "r"(c1) : "memory");
}
__device__ __forceinline__ void prefetch_5d(const CUtensorMap* m, int c0, int c4) {
  asm volatile("cp.async.bulk.prefetch.tensor.5d.L2.global [%0, {%1, %3, %3, %3, %2}];" :: "l"(m), "r"(c0), "r"(c4), "r"(0) : "memory");
}
__device__ __forceinline__ void prefetch_map(const CUtensorMap* m) {
  asm volatile("prefetch.tensormap [%0];" :: "l"(m) : "memory");
}
__device__ __forceinline__ unsigned ld_acquire(const unsigned* p) {
  unsigned v; asm volatile("ld.acquire.gpu.global.u32 %0, [%1];" : "=r"(v) : "l"(p) : "memory"); return v;
}
__device__ __forceinline__ void bar_sync(int id, int n) { asm volatile("bar.sync %0, %1;" :: "r"(id), "r"(n) : "memory"); }
__device__ __forceinline__ void bar_arrive(int id, int n) { asm volatile("bar.arrive %0, %1;" :: "r"(id), "r"(n) : "memory"); }

__device__ __forceinline__ uint64_t make_desc(uint32_t lo) {
  uint64_t d; asm("mov.b64 %0, {%1, %2};" : "=l"(d) : "r"(lo), "r"(0x40000040u)); return d;
}
constexpr uint32_t LBO_K = 1u << 16, LBO_N = (8192u >> 4) << 16;
__device__ __forceinline__ void wgmma_fence() { asm volatile("wgmma.fence.sync.aligned;" ::: "memory"); }
__device__ __forceinline__ void wgmma_commit() { asm volatile("wgmma.commit_group.sync.aligned;" ::: "memory"); }
template <int N> __device__ __forceinline__ void wgmma_wait() { asm volatile("wgmma.wait_group.sync.aligned %0;" :: "n"(N) : "memory"); }

#define R8(a, b) "+f"(a[(b)+0]), "+f"(a[(b)+1]), "+f"(a[(b)+2]), "+f"(a[(b)+3]), "+f"(a[(b)+4]), "+f"(a[(b)+5]), "+f"(a[(b)+6]), "+f"(a[(b)+7])
#define R32(a, b) R8(a, b), R8(a, (b)+8), R8(a, (b)+16), R8(a, (b)+24)
#define W8(a, b) "=f"(a[(b)+0]), "=f"(a[(b)+1]), "=f"(a[(b)+2]), "=f"(a[(b)+3]), "=f"(a[(b)+4]), "=f"(a[(b)+5]), "=f"(a[(b)+6]), "=f"(a[(b)+7])
#define W32(a, b) W8(a, b), W8(a, (b)+8), W8(a, (b)+16), W8(a, (b)+24)
#define N256_REGS \
    "{%0,%1,%2,%3,%4,%5,%6,%7,%8,%9,%10,%11,%12,%13,%14,%15,%16,%17,%18,%19,%20,%21,%22,%23,%24,%25,%26,%27,%28,%29,%30,%31," \
    "%32,%33,%34,%35,%36,%37,%38,%39,%40,%41,%42,%43,%44,%45,%46,%47,%48,%49,%50,%51,%52,%53,%54,%55,%56,%57,%58,%59,%60,%61,%62,%63," \
    "%64,%65,%66,%67,%68,%69,%70,%71,%72,%73,%74,%75,%76,%77,%78,%79,%80,%81,%82,%83,%84,%85,%86,%87,%88,%89,%90,%91,%92,%93,%94,%95," \
    "%96,%97,%98,%99,%100,%101,%102,%103,%104,%105,%106,%107,%108,%109,%110,%111,%112,%113,%114,%115,%116,%117,%118,%119,%120,%121,%122,%123,%124,%125,%126,%127},"
template <int TB> __device__ __forceinline__ void wgmma_n256(float (&d)[128], uint64_t da, uint64_t db) {
  asm volatile("wgmma.mma_async.sync.aligned.m64n256k16.f32.bf16.bf16 " N256_REGS " %128, %129, 1, 1, 1, 0, %130;"
    : R32(d, 0), R32(d, 32), R32(d, 64), R32(d, 96) : "l"(da), "l"(db), "n"(TB));
}
template <int TB> __device__ __forceinline__ void wgmma_n256_first(float (&d)[128], uint64_t da, uint64_t db) {
  asm volatile("wgmma.mma_async.sync.aligned.m64n256k16.f32.bf16.bf16 " N256_REGS " %128, %129, 0, 1, 1, 0, %130;"
    : W32(d, 0), W32(d, 32), W32(d, 64), W32(d, 96) : "l"(da), "l"(db), "n"(TB));
}
template <int TB, bool FIRST> __device__ __forceinline__ void mma_step(float (&acc)[128], uint32_t da, uint32_t db) {
  wgmma_fence();
  if (FIRST) wgmma_n256_first<TB>(acc, make_desc(da), make_desc(db));
  #pragma unroll
  for (int kk = FIRST ? 1 : 0; kk < 4; kk++) wgmma_n256<TB>(acc, make_desc(da + kk * 2), make_desc(db + kk * (TB ? 128 : 2)));
  wgmma_commit();
}
#define N128_REGS \
    "{%0,%1,%2,%3,%4,%5,%6,%7,%8,%9,%10,%11,%12,%13,%14,%15,%16,%17,%18,%19,%20,%21,%22,%23,%24,%25,%26,%27,%28,%29,%30,%31," \
    "%32,%33,%34,%35,%36,%37,%38,%39,%40,%41,%42,%43,%44,%45,%46,%47,%48,%49,%50,%51,%52,%53,%54,%55,%56,%57,%58,%59,%60,%61,%62,%63},"
template <int TB, int OFF> __device__ __forceinline__ void wgmma_n128(float (&d)[128], uint64_t da, uint64_t db) {
  asm volatile("wgmma.mma_async.sync.aligned.m64n128k16.f32.bf16.bf16 " N128_REGS " %64, %65, 1, 1, 1, 0, %66;"
    : R32(d, OFF), R32(d, OFF + 32) : "l"(da), "l"(db), "n"(TB));
}
template <int TB, int OFF> __device__ __forceinline__ void wgmma_n128_first(float (&d)[128], uint64_t da, uint64_t db) {
  asm volatile("wgmma.mma_async.sync.aligned.m64n128k16.f32.bf16.bf16 " N128_REGS " %64, %65, 0, 1, 1, 0, %66;"
    : W32(d, OFF), W32(d, OFF + 32) : "l"(da), "l"(db), "n"(TB));
}
template <int TB, bool FIRST> __device__ __forceinline__ void mma_step128(float (&acc)[128], uint32_t da, uint32_t db) {
  wgmma_fence();
  if (FIRST) {
    wgmma_n128_first<TB, 0>(acc, make_desc(da), make_desc(db));
    wgmma_n128_first<TB, 64>(acc, make_desc(da + 512), make_desc(db));
  }
  #pragma unroll
  for (int kk = FIRST ? 1 : 0; kk < 4; kk++) {
    wgmma_n128<TB, 0>(acc, make_desc(da + kk * 2), make_desc(db + kk * (TB ? 128 : 2)));
    wgmma_n128<TB, 64>(acc, make_desc(da + 512 + kk * 2), make_desc(db + kk * (TB ? 128 : 2)));
  }
  wgmma_commit();
}
__device__ __forceinline__ void wgmma_n8_ta(float (&d)[4], uint64_t da, uint64_t db, int scale_d) {
  asm volatile("{ .reg .pred p; setp.ne.b32 p, %6, 0;\n"
    "wgmma.mma_async.sync.aligned.m64n8k16.f32.bf16.bf16 {%0,%1,%2,%3}, %4, %5, p, 1, 1, 1, 0; }"
    : "+f"(d[0]), "+f"(d[1]), "+f"(d[2]), "+f"(d[3]) : "l"(da), "l"(db), "r"(scale_d));
}
template <int OFF> __device__ __forceinline__ void wgmma_n64(float (&d)[128], uint64_t da, uint64_t db) {
  asm volatile("wgmma.mma_async.sync.aligned.m64n64k16.f32.bf16.bf16 "
    "{%0,%1,%2,%3,%4,%5,%6,%7,%8,%9,%10,%11,%12,%13,%14,%15,%16,%17,%18,%19,%20,%21,%22,%23,%24,%25,%26,%27,%28,%29,%30,%31},"
    " %32, %33, 1, 1, 1, 0, 1;"
    : R32(d, OFF) : "l"(da), "l"(db));
}
template <int OFF> __device__ __forceinline__ void pin32(float (&d)[128]) { asm volatile("" : R32(d, OFF) :: "memory"); }
__device__ __forceinline__ void pin128(float (&d)[128]) { pin32<0>(d); pin32<32>(d); pin32<64>(d); pin32<96>(d); }

__device__ __forceinline__ uint32_t pack2(float lo, float hi) {
  uint32_t r; asm("cvt.rn.bf16x2.f32 %0, %1, %2;" : "=r"(r) : "f"(hi), "f"(lo)); return r;
}
__device__ __forceinline__ float bf_lo(uint32_t w) { return __uint_as_float(w << 16); }
__device__ __forceinline__ float bf_hi(uint32_t w) { return __uint_as_float(w & 0xffff0000u); }
__device__ __forceinline__ float geglu(float ag, float au, float rs, float hrs) {
  const float g = ag * rs;
  const float z = g * fmaf(g * g, 0.0356774081363001f, 0.7978845608028654f);
  float t; asm("tanh.approx.f32 %0, %1;" : "=f"(t) : "f"(z));
  const float w = (g * au) * hrs;
  return fmaf(w, t, w);
}
__device__ __forceinline__ uint4 ldg128(const void* p) {
  uint4 v; asm volatile("ld.global.L1::no_allocate.v4.u32 {%0,%1,%2,%3}, [%4];" : "=r"(v.x), "=r"(v.y), "=r"(v.z), "=r"(v.w) : "l"(p) : "memory"); return v;
}
__device__ __forceinline__ uint4 ld_relaxed(const uint4* p) {
  uint4 v;
  asm volatile("{ .reg .b128 t; ld.relaxed.gpu.global.b128 t, [%4]; mov.b128 {%0,%1,%2,%3}, t; }"
               : "=r"(v.x), "=r"(v.y), "=r"(v.z), "=r"(v.w) : "l"(p) : "memory");
  return v;
}
__device__ __forceinline__ void st_relaxed(uint4* p, uint4 v) {
  asm volatile("{ .reg .b128 t; mov.b128 t, {%1,%2,%3,%4}; st.relaxed.gpu.global.b128 [%0], t; }"
               :: "l"(p), "r"(v.x), "r"(v.y), "r"(v.z), "r"(v.w) : "memory");
}

__device__ __forceinline__ uint2 ld_relaxed2(const uint2* p) {
  uint2 v; asm volatile("ld.relaxed.gpu.global.v2.u32 {%0,%1}, [%2];" : "=r"(v.x), "=r"(v.y) : "l"(p) : "memory"); return v;
}
__device__ __forceinline__ void st_relaxed1(uint32_t* p, uint32_t a) {
  asm volatile("st.relaxed.gpu.global.u32 [%0], %1;" :: "l"(p), "r"(a) : "memory");
}
__device__ __forceinline__ void st_relaxed2(uint2* p, uint32_t a, uint32_t c) {
  asm volatile("st.relaxed.gpu.global.v2.u32 [%0], {%1,%2};" :: "l"(p), "r"(a), "r"(c) : "memory");
}

__device__ __forceinline__ constexpr uint32_t off_b(int u) { return u == 0 ? 0 : (6 + 2 * u) * SLOT; }
__device__ __forceinline__ constexpr uint32_t off_a(int u) { return (2 + u) * SLOT; }

__device__ __forceinline__ float sum8(const uint4& v) {
  return ((bf_lo(v.x) + bf_hi(v.x)) + (bf_lo(v.y) + bf_hi(v.y))) + ((bf_lo(v.z) + bf_hi(v.z)) + (bf_lo(v.w) + bf_hi(v.w)));
}
__device__ __forceinline__ float sq2(uint32_t w, float m, float s) {
  const float a = __uint_as_float(__byte_perm(w, 0, 0x1044)) - m, c = __uint_as_float(__byte_perm(w, 0, 0x3244)) - m;
  return fmaf(c, c, fmaf(a, a, s));
}
__device__ __forceinline__ float reduce8(float v) {
  v += __shfl_xor_sync(0xffffffffu, v, 1);
  v += __shfl_xor_sync(0xffffffffu, v, 2);
  return v + __shfl_xor_sync(0xffffffffu, v, 4);
}

__device__ __forceinline__ uint32_t tagged(float v, uint32_t tag) { return (__float_as_uint(v) & ~1u) | tag; }

template <int TB>
__device__ __forceinline__ void tile_mainloop(float (&acc)[128], uint32_t da0, uint32_t db0,
                                              uint32_t bars, int t, int ring_off, uint32_t rel, bool releaser,
                                              float (&mu)[4], float (&rs)[4], float (&c)[32], uint32_t stat, uint32_t cs) {
  int slot = (8 * t + ring_off) % 6, c6 = (8 * t) % 6;
  uint32_t par = ((8 * t) / 6) & 1;
  if (TB == 0) mbar_wait(bars + MB_X, 0);
  mbar_wait(bars + MB_RFULL + 8 * slot, par);
  PROFC(32 + 8 * t);
  mma_step128<TB, true>(acc, da0, db0 + (8 + slot) * (SLOT >> 4));
  #pragma unroll 1
  for (int k = 1; k < 8; k++) {
    const int ps = slot;
    slot = slot == 5 ? 0 : slot + 1;
    if (++c6 == 6) { c6 = 0; par ^= 1; }
    if (TB == 0) mbar_wait(bars + MB_X + 8 * k, 0);
    mbar_wait(bars + MB_RFULL + 8 * slot, par);
    PROFC(32 + 8 * t + k);
    mma_step128<TB, false>(acc, da0 + k * (SLOT >> 4), db0 + (8 + slot) * (SLOT >> 4));
    if (k == 7) bar_arrive(BAR_ORDER + ((t + 1) & 1), 256);
    wgmma_wait<1>();
    if (releaser) mbar_arrive_cluster(rel + 8 * ps);
  }
  if (TB == 0) {
    wgmma_wait<0>();
    if (releaser) mbar_arrive_cluster(rel + 8 * slot);
  }
  mbar_wait(bars + MB_CS + 8 * t, 0);
  #pragma unroll
  for (int i = 0; i < 4; i++)
    asm volatile("ld.shared.v2.f32 {%0,%1}, [%2];" : "=f"(mu[i]), "=f"(rs[i]) : "r"(stat + ((i >> 1) * 64 + (i & 1) * 8) * 8));
  #pragma unroll
  for (int i = 0; i < 8; i++)
    asm volatile("ld.shared.v4.f32 {%0,%1,%2,%3}, [%4];" : "=f"(c[4 * i]), "=f"(c[4 * i + 1]), "=f"(c[4 * i + 2]), "=f"(c[4 * i + 3])
                 : "r"(cs + (t & 1) * 512 + i * 64));
  wgmma_wait<0>();
  pin128(acc);
  if (TB != 0 && releaser) mbar_arrive_cluster(rel + 8 * slot);
}

__device__ __forceinline__ int cs_index(int p) { return (p & ~15) + ((p >> 1) & 3) * 4 + ((p >> 3) & 1) * 2 + (p & 1); }

__device__ __forceinline__ float link(float v, uint32_t prev, uint32_t zero) {
  return __uint_as_float(__float_as_uint(v) | (prev & zero));
}

__device__ __forceinline__ void sched_fence(uint32_t v, uint32_t zero) {
  asm volatile("{ .reg .pred p; setp.ne.u32 p, %0, 0; @p exit; }" :: "r"(v & zero) : "memory");
}

__device__ __forceinline__ void epilogue_ab(const float (&acc)[128], const float (&c)[32], const float (&mu)[4], const float (&rs)[4],
                                            float sign, uint4* dst, uint32_t zero) {
  uint32_t prev = 0;
  #pragma unroll
  for (int rr = 0; rr < 4; rr++) {
    const float sc = sign * rs[rr];
    #pragma unroll
    for (int m = 0; m < 4; m++) {
      uint32_t w[4];
      #pragma unroll
      for (int ii = 0; ii < 4; ii++) {
        const int i = 4 * m + ii, a = 64 * (rr >> 1) + 4 * i + 2 * (rr & 1);
        const float mm = link(mu[rr], prev, zero);
        prev = w[ii] = pack2(fmaf(-mm, c[2 * i], acc[a]) * sc, fmaf(-mm, c[2 * i + 1], acc[a + 1]) * sc);
      }
      dst[(rr >> 1) * 8 * D + (rr & 1) * D + m * 4] = make_uint4(w[0], w[1], w[2], w[3]);
      sched_fence(w[2], zero);
    }
  }
}
__device__ __forceinline__ void epilogue_gu(const float (&acc)[128], const float (&c)[32], const float (&mu)[4], const float (&rs)[4],
                                            uint4* dst, uint32_t zero) {
  uint32_t prev = 0;
  #pragma unroll
  for (int rr = 0; rr < 4; rr++) {
    const float hrs = 0.5f * rs[rr];
    #pragma unroll
    for (int m = 0; m < 2; m++) {
      uint32_t w[4];
      #pragma unroll
      for (int ii = 0; ii < 4; ii++) {
        const int i = 4 * m + ii, a = 64 * (rr >> 1) + 4 * i + 2 * (rr & 1);
        const float mm = link(mu[rr], prev, zero);
        prev = w[ii] = pack2(geglu(fmaf(-mm, c[2 * i], acc[a]), fmaf(-mm, c[16 + 2 * i], acc[a + 32]), rs[rr], hrs),
                             geglu(fmaf(-mm, c[2 * i + 1], acc[a + 1]), fmaf(-mm, c[17 + 2 * i], acc[a + 33]), rs[rr], hrs));
      }
      dst[(rr >> 1) * 8 * F + (rr & 1) * F + m * 4] = make_uint4(w[0], w[1], w[2], w[3]);
      sched_fence(w[2], zero);
    }
  }
}

__device__ __forceinline__ void side_jobs(const Ptrs& ptrs, int b, int r, int j, int warp, int lane) {
  const int row = r * 128 + j * 16 + warp * 4 + (lane >> 3);
  const int col = r * 8 + warp * 2 + (lane >> 4);
  const __nv_bfloat16* px = ptrs.x + (size_t)row * D + (lane & 7) * 8;
  const __nv_bfloat16* ph = ((j & 4) ? ptrs.hi : ptrs.hr) + (size_t)((j & 3) * 128 + col) * D + (lane & 15) * 8;
  uint4 v[8], w[4];
  #pragma unroll
  for (int i = 0; i < 8; i++) v[i] = ldg128(px + i * 64);
  #pragma unroll
  for (int i = 0; i < 4; i++) w[i] = ldg128(ph + i * 128);
  const uint32_t tag = (*reinterpret_cast<const volatile unsigned*>(ptrs.epoch + b) + 1) & 1;
  float s = 0.f;
  #pragma unroll
  for (int i = 0; i < 8; i++) s += sum8(v[i]);
  const float mu = reduce8(s) * (1.f / D);
  float q0 = 0.f, q1 = 0.f;
  #pragma unroll
  for (int i = 0; i < 8; i++) { q0 = sq2(v[i].y, mu, sq2(v[i].x, mu, q0)); q1 = sq2(v[i].w, mu, sq2(v[i].z, mu, q1)); }
  const float rs = rsqrtf(reduce8(q0 + q1) * (1.f / D) + 1e-5f);
  if ((lane & 7) == 0) st_relaxed2(ptrs.stat + row, tagged(mu, tag), tagged(rs, tag));
  s = reduce8((sum8(w[0]) + sum8(w[1])) + (sum8(w[2]) + sum8(w[3])));
  s += __shfl_xor_sync(0xffffffffu, s, 8);
  const int p = (col & ~0x1e) | ((col & 6) << 2) | ((col >> 2) & 6);
  if ((lane & 15) == 0) st_relaxed1(reinterpret_cast<uint32_t*>(ptrs.cs + j * 32) + cs_index(p), tagged(s, tag));
}

template <int N> __device__ __forceinline__ void gather(const uint4* (&src)[N], const uint32_t (&dst)[N], uint32_t tag) {
  uint4 v[N];
  #pragma unroll 1
  for (int spins = 0; spins < SPIN_LIMIT; spins++) {
    uint32_t bad = 0;
    #pragma unroll
    for (int i = 0; i < N; i++) v[i] = ld_relaxed(src[i]);
    #pragma unroll
    for (int i = 0; i < N; i++) bad |= (v[i].x ^ tag) | (v[i].y ^ tag) | (v[i].z ^ tag) | (v[i].w ^ tag);
    if (__all_sync(0xffffffffu, (bad & 1) == 0)) break;
    __nanosleep(50);
  }
  #pragma unroll
  for (int i = 0; i < N; i++)
    asm volatile("st.shared.v4.u32 [%0], {%1,%2,%3,%4};"
                 :: "r"(dst[i]), "r"(v[i].x & ~1u), "r"(v[i].y & ~1u), "r"(v[i].z & ~1u), "r"(v[i].w & ~1u) : "memory");
}

__device__ __forceinline__ void helper_cta(const Maps& maps, const Ptrs& ptrs, uint8_t* smem, int hb, int tid) {
  const uint32_t base = smem_u32(smem), bars = base + SMEM_BAR;
  auto tile_of = [&](int i) {
    const int j = i < 6 ? 2 * hb + (i & 1) : hb;
    return (j < 4 ? 4 * j : 3 * j + 4) + (i >> 1);
  };
  if (tid == 0)
    for (int u = 0; u < 12; u++) { mbar_init(bars + 8 * u, 1); mbar_init(bars + 96 + 8 * u, 2); }
  if (tid < 256) reinterpret_cast<uint32_t*>(smem + 12 * SLOT)[tid] = 0x3F803F80u;
  asm volatile("fence.proxy.async.shared::cta;" ::: "memory");
  __syncthreads();
  if (tid == 256) {
    for (int s = 0; s < 56; s++) {
      const int u = s % 12;
      mbar_wait(bars + 96 + 8 * u, ((s / 12) & 1) ^ 1);
      mbar_expect_tx(bars + 8 * u, SLOT);
      tma_2d(base + u * SLOT, &maps.wg, tile_of(s >> 3) * 64, (s & 7) * 64, bars + 8 * u);
      tma_2d(base + u * SLOT + 8192, &maps.wu, tile_of(s >> 3) * 64, (s & 7) * 64, bars + 8 * u);
    }
  } else if (tid < 256) {
    const unsigned epoch = ptrs.epoch[NCTA + hb] + 1;
    const int mat = __shfl_sync(0xffffffffu, tid >> 7, 0);
    const uint32_t d0 = (base & 0x3FFFF) >> 4;
    const int p = mat * 64 + ((tid >> 5) & 3) * 16 + ((tid & 31) >> 2);
    float acc[4];
    for (int i = 0; i < 7; i++) {
      #pragma unroll 1
      for (int k = 0; k < 8; k++) {
        const int s = i * 8 + k, u = s % 12;
        mbar_wait(bars + 8 * u, (s / 12) & 1);
        wgmma_fence();
        #pragma unroll
        for (int kk = 0; kk < 4; kk++)
          wgmma_n8_ta(acc, make_desc(d0 + LBO_N + u * (SLOT >> 4) + mat * 512 + kk * 128), make_desc(d0 + LBO_K + 12 * (SLOT >> 4)), (k | kk) != 0);
        wgmma_commit();
        wgmma_wait<0>();
        if ((tid & 127) == 0) mbar_arrive(bars + 96 + 8 * u);
      }
      asm volatile("" : "+f"(acc[0]), "+f"(acc[2]) :: "memory");
      if ((tid & 3) == 0) {
        uint32_t* dst = reinterpret_cast<uint32_t*>(ptrs.cs + (8 + tile_of(i)) * 32);
        st_relaxed1(dst + cs_index(p), tagged(acc[0], epoch & 1));
        st_relaxed1(dst + cs_index(p + 8), tagged(acc[2], epoch & 1));
      }
    }
    bar_sync(1, 256);
    if (tid == 0) ptrs.epoch[NCTA + hb] = epoch;
  }
}

template <int P> __device__ __forceinline__ void ship_quarter(const float (&acc)[128], uint4* dst, uint32_t tag, uint32_t zero) {
  #pragma unroll
  for (int i = 0; i < 4; i++) {
    uint32_t w[4];
    #pragma unroll
    for (int e = 0; e < 4; e++) w[e] = pack2(acc[32 * P + 8 * i + 2 * e], acc[32 * P + 8 * i + 2 * e + 1]);
    w[P] = (__byte_perm(w[P], __float_as_uint(acc[32 * P + 8 * i + 2 * P]), 0x3276) & ~1u) | tag;
    st_relaxed(dst + i * 256, make_uint4(w[0], w[1], w[2], w[3]));
  }
  sched_fence(__float_as_uint(acc[32 * P]), zero);
}
__device__ __forceinline__ void recv_issue(uint4 (&in)[4], const uint4* src) {
  #pragma unroll
  for (int i = 0; i < 4; i++) in[i] = ld_relaxed(src + i * 256);
}
template <int P> __device__ __forceinline__ uint32_t& tag_word(uint4& v) { return P == 0 ? v.x : (P == 1 ? v.y : v.z); }
template <int P> __device__ __forceinline__ void recv_poll(const uint4* src, uint32_t tag) {
  if ((threadIdx.x & 31) == 31) {
    #pragma unroll 1
    for (int spins = 0; spins < SPIN_LIMIT; spins++) {
      uint4 v = ld_relaxed(src + 3 * 256);
      if (((tag_word<P>(v) ^ tag) & 1) == 0) break;
    }
  }
  __syncwarp();
}
template <int P> __device__ __forceinline__ void recv_add(float (&s)[32], uint4 (&in)[4], const uint4* src, uint32_t tag) {
  #pragma unroll 1
  for (int spins = 0; spins < 64; spins++) {
    const uint32_t bad = (tag_word<P>(in[0]) ^ tag) | (tag_word<P>(in[1]) ^ tag) | (tag_word<P>(in[2]) ^ tag) | (tag_word<P>(in[3]) ^ tag);
    if (__all_sync(0xffffffffu, (bad & 1) == 0)) break;
    recv_poll<P>(src, tag);
    recv_issue(in, src);
  }
  #pragma unroll
  for (int i = 0; i < 4; i++) {
    tag_word<P>(in[i]) |= 1u;
    s[8 * i + 0] += bf_lo(in[i].x); s[8 * i + 1] += bf_hi(in[i].x);
    s[8 * i + 2] += bf_lo(in[i].y); s[8 * i + 3] += bf_hi(in[i].y);
    s[8 * i + 4] += bf_lo(in[i].z); s[8 * i + 5] += bf_hi(in[i].z);
    s[8 * i + 6] += bf_lo(in[i].w); s[8 * i + 7] += bf_hi(in[i].w);
  }
}

template <int P> __device__ __forceinline__ void tail_quarter(float (&acc)[128], uint32_t da0, uint32_t db0, uint32_t bars,
                                                              uint32_t phase) {
  #pragma unroll
  for (int st = 0; st < 4; st++) {
    const int u = (1 + st) & 3;
    const bool w = (P == 0) || (P == 2 && st == 3);
    if (P == 0) { if (st < 3) mbar_wait(bars + 8 * u, (phase >> u) & 1); else mbar_wait(bars + MB_EARLY, 0); }
    if (P == 2 && st == 3) mbar_wait(bars, phase & 1);
    if (w || st == 0) wgmma_fence();
    const uint32_t oa = st < 3 ? off_a(u) : 6 * SLOT;
    const uint32_t ob = (st < 3 ? off_b(u) : (P < 2 ? 7 * SLOT : 0)) + P * 8192;
    #pragma unroll
    for (int kk = 0; kk < 4; kk++)
      wgmma_n64<32 * P>(acc, make_desc(da0 + (oa >> 4) + kk * 2), make_desc(db0 + (ob >> 4) + kk * 128));
  }
  wgmma_commit();
}

__global__ void __cluster_dims__(2, 1, 1) __launch_bounds__(NTHREADS, 1)
fused_kernel(const __grid_constant__ Ptrs ptrs, const __grid_constant__ Maps maps) {
  extern __shared__ __align__(1024) uint8_t smem_raw[];
  const uint32_t base = smem_u32(smem_raw);
  const uint32_t bars = base + SMEM_BAR;
  const int tid = threadIdx.x, wg = __shfl_sync(0xffffffffu, tid >> 7, 0), lane = tid & 31;
  const int b = blockIdx.x, rank = b & 1, rp = (b >> 1) & 7;
  const int r = 2 * rp + rank, j = b >> 4, n = j & 1, kq = j >> 1;
  const int ntiles = j < 4 ? 5 : 4;
  const int gu0 = j < 4 ? 4 * j - 1 : 3 * j + 3;
  const int nd = j < 4 ? 14 : 18, d0 = j < 4 ? 14 * kq : 18 * kq - 8;
  const int nsteps1 = ntiles * 8, nsteps2 = nd + 7;
  const int ring_off = j < 4 ? 2 : 4;

  if (b >= NCTA) {
    helper_cta(maps, ptrs, smem_raw, b - NCTA, tid);
    return;
  }
  const CUtensorMap* mh = (j & 4) ? &maps.hi : &maps.hr;
  if (tid == 0) PROF(0, 0);
  if (tid == 256) {
    prefetch_map(&maps.x);
    prefetch_map(mh);
    for (int u = 0; u < 8; u++) mbar_init(bars + MB_X + 8 * u, 1);
    for (int u = 0; u < 6; u++) { mbar_init(bars + MB_RFULL + 8 * u, 1); mbar_init(bars + MB_REMPTY + 8 * u, 2); }
    for (int u = 0; u < 4; u++) { mbar_init(bars + 8 * u, 1); mbar_init(bars + MB_EMPTY + 8 * u, 4); }
    for (int i = 0; i < 3; i++) mbar_init(bars + MB_EARLY + 8 * i, 1);
    for (int i = 0; i < 5; i++) mbar_init(bars + MB_CS + 8 * i, 1);
    *reinterpret_cast<volatile uint32_t*>(smem_raw + SMEM_BAR + SM_PROG) = 0;
    asm volatile("fence.mbarrier_init.release.cluster;" ::: "memory");
    PROF(2, 6);
  }
  __syncwarp();
  asm volatile("barrier.cluster.arrive.relaxed.aligned;" ::: "memory");
  if (tid == 256) {
    #pragma unroll
    for (int k = 0; k < 2; k++) {
      const uint32_t full = bars + MB_RFULL + 8 * (k + ring_off), sb = base + (8 + k + ring_off) * SLOT;
      mbar_expect_tx(bars + MB_X + 8 * k, SLOT);
      tma_2d(base + k * SLOT, &maps.x, k * 64, r * 128, bars + MB_X + 8 * k);
      mbar_expect_tx(full, SLOT);
      tma_5d(sb, mh, k * 64, (j & 3) * 4, full);
      tma_5d(sb + 8192, mh, k * 64, (j & 3) * 4 + 2, full);
    }
    PROF(2, 7);
  }
  __syncwarp();
  if (wg == ((ntiles + 1) & 1)) side_jobs(ptrs, b, r, j, (tid >> 5) & 3, lane);

  if (wg == 2) {
    asm volatile("setmaxnreg.dec.sync.aligned.u32 40;");
    const int warp = __shfl_sync(0xffffffffu, (tid >> 5) & 3, 0);
    const int c0 = n * 256 + ((kq + 1 + 2 * rank) & 3) * 64, c1 = n * 256 + ((kq + 2 + 2 * rank) & 3) * 64;
    if (warp == 0) {
      asm volatile("barrier.cluster.wait.aligned;" ::: "memory");
      if (lane == 0) {
        volatile uint32_t* prog = reinterpret_cast<volatile uint32_t*>(smem_raw + SMEM_BAR + SM_PROG);
        int slot = (ring_off + 2) % 6;
        for (int s = 2; s < 8; s++) {
          if (s < 6) {
            mbar_expect_tx(bars + MB_X + 8 * s, SLOT);
            tma_2d(base + s * SLOT, &maps.x, s * 64, r * 128, bars + MB_X + 8 * s);
          } else {
            mbar_wait(bars + MB_REMPTY + 8 * slot, 0);
          }
          PROF(2, 32 + s);
          mbar_expect_tx(bars + MB_RFULL + 8 * slot, SLOT);
          tma_5d_mc(base + (8 + slot) * SLOT + rank * 8192, mh, s * 64, (j & 3) * 4 + rank * 2, bars + MB_RFULL + 8 * slot, W_POLICY);
          if (s == 5) {
            for (int k = 6; k < 8; k++) {
              mbar_expect_tx(bars + MB_X + 8 * k, SLOT);
              tma_2d(base + k * SLOT, &maps.x, k * 64, r * 128, bars + MB_X + 8 * k);
            }
          }
          slot = slot == 5 ? 0 : slot + 1;
        }
        const CUtensorMap* mw = rank ? &maps.wu : &maps.wg;
        int c6 = 2;
        uint32_t par = 0;
        #pragma unroll 1
        for (int s = 8; s < nsteps1; s++) {
          mbar_wait(bars + MB_REMPTY + 8 * slot, par);
          PROF(2, 32 + s);
          mbar_expect_tx(bars + MB_RFULL + 8 * slot, SLOT);
          tma_2d_mc(base + (8 + slot) * SLOT + rank * 8192, mw, (gu0 + (s >> 3)) * 64, (s & 7) * 64, bars + MB_RFULL + 8 * slot, W_POLICY);
          *prog = s;
          slot = slot == 5 ? 0 : slot + 1;
          if (++c6 == 6) { c6 = 0; par ^= 1; }
        }
        PROF(2, 1);
        mbar_wait(bars + MB_AB, 0);
        PROF(2, 2);
        #pragma unroll 1
        for (int t = 0; t < nd; t++) {
          const int u = t & 3, ds = d0 + t;
          if (t < 4) {
            const int last = t == 0 ? 0 : 2 * t - 1;
            mbar_wait(bars + MB_REMPTY + 8 * last, ((nsteps1 - 6 + last) / 6) & 1);
          } else {
            mbar_wait(bars + MB_EMPTY + 8 * u, ((t >> 2) - 1) & 1);
          }
          PROF(2, 80 + t);
          const uint32_t full = bars + 8 * u, sb = base + off_b(u) + rank * SLOT;
          mbar_expect_tx(full, 3 * SLOT);
          tma_2d(base + off_a(u), ds < 32 ? &maps.cr : &maps.ci, (ds & 31) * 64, r * 128, full, C_POLICY);
          tma_2d_mc(sb, &maps.ab, c0, ds * 64, full);
          tma_2d_mc(sb + 8192, &maps.ab, c1, ds * 64, full);
          *prog = nsteps1 + 2 * t;
        }
        PROF(2, 3);
        mbar_wait(bars + MB_H, 0);
        PROF(2, 4);
        #pragma unroll 1
        for (int t = nd; t < nsteps2; t++) {
          const int u = t & 3, fs = kq * 7 + t - nd;
          mbar_wait(bars + MB_EMPTY + 8 * u, ((t >> 2) - 1) & 1);
          PROF(2, 80 + t);
          const uint32_t full = bars + 8 * u, sb = base + off_b(u) + rank * SLOT, sa = base + off_a(u);
          if (t < nsteps2 - 1) {
            mbar_expect_tx(full, 3 * SLOT);
            tma_2d(sa, &maps.h, fs * 64, r * 128, full);
            tma_5d_mc(sb, &maps.wd, c0, fs * 2, full);
            tma_5d_mc(sb + 8192, &maps.wd, c1, fs * 2, full);
          } else {
            mbar_expect_tx(full, 2 * SLOT);
            tma_5d_mc(base + SLOT + rank * 8192, &maps.wd, n * 256 + ((kq + 3 + rank) & 3) * 64, fs * 2, full);
            tma_2d(sa, &maps.x, n * 256 + kq * 64, r * 128, full);
          }
          if (t == nd + 1) {
            mbar_expect_tx(bars + MB_EARLY, 2 * SLOT);
            tma_2d(base + 6 * SLOT, &maps.h, (kq * 7 + 6) * 64, r * 128, bars + MB_EARLY);
            tma_5d_mc(base + 7 * SLOT + rank * 8192, &maps.wd, n * 256 + ((kq + 1 + rank) & 3) * 64, (kq * 7 + 6) * 2, bars + MB_EARLY);
          }
        }
        PROF(2, 5);
        ptrs.epoch[b] += 1;
      }
    } else {
      if (warp == 1 && lane < 11) prefetch_map(&maps.cr + lane);
      asm volatile("barrier.cluster.wait.aligned;" ::: "memory");
      if (warp == 1) {
        for (int t = 0; t < ntiles; t++) {
          bar_sync(BAR_PUB + t, 192);
          if (lane == 0) {
            asm volatile("fence.proxy.async;" ::: "memory");
            __threadfence();
            atomicAdd(&ptrs.cnt[t == 0 ? 16 * 32 : r * 32], 1u);
            PROF(2, 15 + t);
          }
          __syncwarp();
        }
      } else if (warp == 2) {
        const uint32_t tag = (ptrs.epoch[b] + 1) & 1;
        if (lane == 0) *reinterpret_cast<volatile uint32_t*>(smem_raw + SMEM_BAR + SM_TAG) = tag;
        const uint4* stat = reinterpret_cast<const uint4*>(ptrs.stat + r * 128) + lane;
        const uint4* src3[3] = {stat, stat + 32, ptrs.cs + j * 32 + lane};
        const uint32_t dst3[3] = {base + SMEM_STAT + lane * 16, base + SMEM_STAT + 512 + lane * 16, base + SMEM_CS + lane * 16};
        gather<3>(src3, dst3, tag);
        __syncwarp();
        if (lane == 0) { mbar_arrive(bars + MB_CS); PROF(2, 25); }
        for (int t = 1; t < ntiles + 2; t++) {
          if (t >= 2) bar_sync(BAR_PUB + t - 2, 192);
          if (t < ntiles) {
            const uint4* src[1] = {ptrs.cs + (8 + gu0 + t) * 32 + lane};
            const uint32_t dst[1] = {base + SMEM_CS + (t & 1) * 512 + lane * 16};
            gather<1>(src, dst, tag);
            __syncwarp();
            if (lane == 0) { mbar_arrive(bars + MB_CS + 8 * t); PROF(2, 25 + t); }
          }
        }
      } else if (lane == 0) {
        const unsigned epoch = ptrs.epoch[b] + 1;
        const volatile uint32_t* prog = reinterpret_cast<const volatile uint32_t*>(smem_raw + SMEM_BAR + SM_PROG);
        int next = 0, stage = 0;
        #pragma unroll 1
        for (int spins = 0; spins < SPIN_LIMIT && (stage < 2 || next < nsteps2); spins++) {
          const int upto = ((int)*prog - nsteps1) / 2 + PF2_DIST;
          for (; next < nsteps2 && (next <= upto || upto >= nd - 1 + PF2_DIST); next++) {
            if (next < nd) {
              if ((next & 1) == n) prefetch_2d(d0 + next < 32 ? &maps.cr : &maps.ci, ((d0 + next) & 31) * 64, r * 128);
            } else if ((next & 7) == rp) {
              prefetch_5d(&maps.wd, c0, (kq * 7 + next - nd) * 2);
              prefetch_5d(&maps.wd, c1, (kq * 7 + next - nd) * 2);
            }
          }
          if (stage < 2) {
            const unsigned* cnt = &ptrs.cnt[stage == 0 ? 16 * 32 : r * 32];
            if ((int)(*reinterpret_cast<const volatile unsigned*>(cnt) - epoch * (stage == 0 ? 128 : 28)) >= 0) {
              ld_acquire(cnt);
              asm volatile("fence.proxy.async;" ::: "memory");
              mbar_arrive(bars + MB_AB + 8 * stage);
              PROF(2, 23 + stage);
              stage++;
            }
          }
          __nanosleep(100);
        }
      }
    }
  } else {
    asm volatile("setmaxnreg.inc.sync.aligned.u32 232;");
    const uint32_t zero = ptrs.zero;
    const int warp = __shfl_sync(0xffffffffu, (tid >> 5) & 3, 0), g = lane >> 2, q = lane & 3;
    const uint32_t peer_bars = mapa(bars, lane & 1);
    const bool releaser = (tid & 127) < 2;
    const uint32_t d_base = (base & 0x3FFFF) >> 4;
    const uint32_t db0 = d_base + LBO_N, da0 = d_base + wg * 512 + LBO_K;
    float acc[128];

    {
      const int t0 = (wg + ntiles) & 1;
      const int row = r * 128 + warp * 16 + g;
      PROFC(1);
      asm volatile("barrier.cluster.wait.aligned;" ::: "memory");
      const uint32_t stat = base + SMEM_STAT + (warp * 16 + g) * 8, cs = base + SMEM_CS + q * 16;
      for (int t = t0; t < ntiles; t += 2) {
        float mu[4], rs[4], c[32];
        if (t > 0) {
          bar_sync(BAR_ORDER + (t & 1), 256);
          tile_mainloop<1>(acc, d_base + LBO_K, db0, bars, t, ring_off, peer_bars + MB_REMPTY, releaser, mu, rs, c, stat, cs);
        } else {
          tile_mainloop<0>(acc, d_base + LBO_K, d_base + LBO_K, bars, t, ring_off, peer_bars + MB_REMPTY, releaser, mu, rs, c, stat, cs);
        }
        PROFC(16 + 2 * t);
        if (t == 0)
          epilogue_ab(acc, c, mu, rs, (j & 4) ? -1.f : 1.f,
                      reinterpret_cast<uint4*>(ptrs.ab + (size_t)((j >> 2) * S + row) * D + (j & 3) * 128 + q * 8), zero);
        else
          epilogue_gu(acc, c, mu, rs, reinterpret_cast<uint4*>(ptrs.h + (size_t)row * F + (gu0 + t) * 64 + q * 8), zero);
        bar_arrive(BAR_PUB + t, 192);
        PROFC(17 + 2 * t);
      }
    }

    if (wg == 0) bar_sync(BAR_ORDER + (ntiles & 1), 256);
    const uint32_t rel = peer_bars + MB_EMPTY;
    mbar_wait(bars, 0);
    PROFC(80);
    mma_step<1, true>(acc, da0 + (off_a(0) >> 4), db0 + (off_b(0) >> 4));
    #pragma unroll 1
    for (int t = 1; t < nsteps2 - 4; t++) {
      const int u = t & 3;
      mbar_wait(bars + 8 * u, (t >> 2) & 1);
      PROFC(80 + t);
      mma_step<1, false>(acc, da0 + (off_a(u) >> 4), db0 + (off_b(u) >> 4));
      wgmma_wait<1>();
      if (releaser) mbar_arrive_cluster(rel + 8 * ((t - 1) & 3));
    }
    wgmma_wait<0>();
    pin128(acc);
    if (releaser) mbar_arrive_cluster(rel);
    PROFC(8);
    const uint32_t phase = ((nsteps2 - 4) >> 2) & 1 ? 0xEu : 0x1u;

    #pragma unroll
    for (int i = 0; i < 128; i++) { float v; asm volatile("mov.b32 %0, %1;" : "=f"(v) : "f"(acc[i])); acc[i] = v; }
    const int bq = b & 31;
    const uint32_t tag = *reinterpret_cast<volatile uint32_t*>(smem_raw + SMEM_BAR + SM_TAG);
    const uint4* inbox = ptrs.part + b * 3072 + tid;
    uint4 in0[4], in1[4], in2[4];
    float sum[32];
    if (wg == 1) bar_sync(BAR_TAIL, 256);
    tail_quarter<0>(acc, da0, db0, bars, phase);
    if (wg == 0) bar_arrive(BAR_TAIL, 256);
    wgmma_wait<0>(); pin32<0>(acc);
    ship_quarter<0>(acc, ptrs.part + ((bq + 32 * ((kq + 1) & 3)) * 3 + 0) * 1024 + tid, tag, zero);
    PROFC(9);
    tail_quarter<1>(acc, da0, db0, bars, phase);
    wgmma_wait<0>(); pin32<32>(acc);
    ship_quarter<1>(acc, ptrs.part + ((bq + 32 * ((kq + 2) & 3)) * 3 + 1) * 1024 + tid, tag, zero);
    PROFC(10);
    tail_quarter<2>(acc, da0, db0, bars, phase);
    recv_issue(in0, inbox);
    wgmma_wait<0>(); pin32<64>(acc);
    ship_quarter<2>(acc, ptrs.part + ((bq + 32 * ((kq + 3) & 3)) * 3 + 2) * 1024 + tid, tag, zero);
    PROFC(11);
    tail_quarter<3>(acc, da0, db0, bars, phase);
    recv_issue(in1, inbox + 1024);
    const uint32_t xrow = base + off_a(0) + (wg * 64 + warp * 16 + (lane & 15)) * 128;
    #pragma unroll
    for (int i = 0; i < 4; i++) {
      uint32_t xr[4];
      asm volatile("ldmatrix.sync.aligned.m8n8.x4.shared.b16 {%0,%1,%2,%3}, [%4];"
                   : "=r"(xr[0]), "=r"(xr[1]), "=r"(xr[2]), "=r"(xr[3])
                   : "r"(xrow + (((2 * i + (lane >> 4)) ^ (lane & 7)) << 4)) : "memory");
      #pragma unroll
      for (int e = 0; e < 4; e++) { sum[8 * i + 2 * e] = bf_lo(xr[e]); sum[8 * i + 2 * e + 1] = bf_hi(xr[e]); }
    }
    recv_add<0>(sum, in0, inbox, tag);
    wgmma_wait<0>(); pin32<96>(acc);
    PROFC(12);
    #pragma unroll
    for (int i = 0; i < 32; i++) sum[i] += acc[96 + i];
    recv_add<1>(sum, in1, inbox + 1024, tag);
    recv_poll<2>(inbox + 2048, tag);
    recv_issue(in2, inbox + 2048);
    recv_add<2>(sum, in2, inbox + 2048, tag);
    PROFC(14);
    __syncwarp();
    #pragma unroll
    for (int i = 0; i < 4; i++)
      asm volatile("stmatrix.sync.aligned.m8n8.x4.shared.b16 [%0], {%1,%2,%3,%4};"
                   :: "r"(xrow + (((2 * i + (lane >> 4)) ^ (lane & 7)) << 4)),
                      "r"(pack2(sum[8 * i], sum[8 * i + 1])), "r"(pack2(sum[8 * i + 2], sum[8 * i + 3])),
                      "r"(pack2(sum[8 * i + 4], sum[8 * i + 5])), "r"(pack2(sum[8 * i + 6], sum[8 * i + 7])) : "memory");
    asm volatile("fence.proxy.async.shared::cta;" ::: "memory");
    __syncwarp();
    if (lane == 0) {
      tma_store_2d(&maps.out, base + off_a(0) + (wg * 64 + warp * 16) * 128, n * 256 + kq * 64, r * 128 + wg * 64 + warp * 16);
      asm volatile("cp.async.bulk.commit_group;" ::: "memory");
      asm volatile("cp.async.bulk.wait_group.read 0;" ::: "memory");
    }
    PROFC(13);
  }
}

typedef CUresult (*EncodeFn)(CUtensorMap*, CUtensorMapDataType, cuuint32_t, void*, const cuuint64_t*, const cuuint64_t*,
                             const cuuint32_t*, const cuuint32_t*, CUtensorMapInterleave, CUtensorMapSwizzle,
                             CUtensorMapL2promotion, CUtensorMapFloatOOBfill);

void encode(EncodeFn fn, CUtensorMap* m, const void* ptr, int rank, const cuuint64_t* dims, const cuuint64_t* strides,
            const cuuint32_t* box) {
  const cuuint32_t es[5] = {1, 1, 1, 1, 1};
  fn(m, CU_TENSOR_MAP_DATA_TYPE_BFLOAT16, rank, const_cast<void*>(ptr), dims, strides, box, es,
     CU_TENSOR_MAP_INTERLEAVE_NONE, CU_TENSOR_MAP_SWIZZLE_128B, CU_TENSOR_MAP_L2_PROMOTION_L2_128B,
     CU_TENSOR_MAP_FLOAT_OOB_FILL_NONE);
}
void map_2d(EncodeFn fn, CUtensorMap* m, const void* ptr, int cols, int rows, int box_rows) {
  const cuuint64_t dims[2] = {(cuuint64_t)cols, (cuuint64_t)rows}, strides[1] = {(cuuint64_t)cols * 2};
  const cuuint32_t box[2] = {64, (cuuint32_t)box_rows};
  encode(fn, m, ptr, 2, dims, strides, box);
}
void map_perm(EncodeFn fn, CUtensorMap* m, const void* ptr, int rows, int box_groups) {
  const cuuint64_t dims[5] = {512, 2, 4, 4, (cuuint64_t)rows / 32}, strides[4] = {1024, 8 * 1024, 2 * 1024, 32 * 1024};
  const cuuint32_t box[5] = {64, 2, 4, 4, (cuuint32_t)box_groups};
  encode(fn, m, ptr, 5, dims, strides, box);
}

}

extern "C" void kernel_launch(void* const* d_in, const int* in_sizes, int n_in, void* d_out, int out_size) {
  void* fnp = nullptr;
  cudaDriverEntryPointQueryResult qr;
  cudaGetDriverEntryPoint("cuTensorMapEncodeTiled", &fnp, cudaEnableDefault, &qr);
  EncodeFn fn = (EncodeFn)fnp;
  void *p_ab, *p_h, *p_part, *p_cs, *p_stat, *p_cnt, *p_epoch;
  cudaGetSymbolAddress(&p_ab, g_ab);
  cudaGetSymbolAddress(&p_h, g_h);
  cudaGetSymbolAddress(&p_part, g_part);
  cudaGetSymbolAddress(&p_cs, g_cs);
  cudaGetSymbolAddress(&p_stat, g_stat);
  cudaGetSymbolAddress(&p_cnt, g_cnt);
  cudaGetSymbolAddress(&p_epoch, g_epoch);
  Maps maps;
  map_2d(fn, &maps.cr, d_in[1], S, S, 128);
  map_2d(fn, &maps.ci, d_in[2], S, S, 128);
  map_2d(fn, &maps.h, p_h, F, S, 128);
  map_perm(fn, &maps.hr, d_in[3], D, 2);
  map_perm(fn, &maps.hi, d_in[4], D, 2);
  map_2d(fn, &maps.wg, d_in[6], F, D, 64);
  map_2d(fn, &maps.wu, d_in[7], F, D, 64);
  map_perm(fn, &maps.wd, d_in[8], F, 2);
  map_2d(fn, &maps.ab, p_ab, D, 2 * S, 64);
  map_2d(fn, &maps.x, d_in[0], D, S, 128);
  map_2d(fn, &maps.out, d_out, D, S, 16);
  const Ptrs ptrs = {(const __nv_bfloat16*)d_in[0], (const __nv_bfloat16*)d_in[3], (const __nv_bfloat16*)d_in[4],
                     (__nv_bfloat16*)p_ab, (__nv_bfloat16*)p_h, (uint4*)p_part, (uint4*)p_cs, (uint2*)p_stat,
                     (unsigned*)p_cnt, (unsigned*)p_epoch, 0u};
  cudaFuncSetAttribute(fused_kernel, cudaFuncAttributeMaxDynamicSharedMemorySize, SMEM_TOTAL);
  fused_kernel<<<NCTA + NHELP, NTHREADS, SMEM_TOTAL, cudaStreamPerThread>>>(ptrs, maps);
}
```

```cpp
#include <cuda_runtime.h>
#include <cuda.h>
#include <cuda_bf16.h>
#include <stdint.h>

namespace {

constexpr int S = 2048, D = 512, F = 1792;
constexpr int NCTA = 128, NHELP = 4, NTHREADS = 384;
constexpr int SLOT = 16384;
constexpr int SMEM_STAT = 14 * SLOT;
constexpr int SMEM_CS = SMEM_STAT + 1024;
constexpr int SMEM_BAR = SMEM_CS + 1024;
constexpr int SMEM_TOTAL = SMEM_BAR + 1024;
constexpr int MB_EMPTY = 0, MB_AREG = 32;
constexpr int MB_REMPTY = 80, MB_HS = 128;
constexpr int MB_FULL = 200, MB_RFULL = 232, MB_EARLY = 280, MB_AB = 288, MB_H = 296, MB_TAG = 304, MB_XOUT = 312;
constexpr int MB_X = 320, MB_CS = 384;
constexpr int SM_PROG = 440, SM_TAG = 444;
constexpr int BAR_ORDER = 1, BAR_TAIL = 3, BAR_PUB = 4;
#define PF2_DIST 4
#define AB_LINK 2
#define DEFER 3
#define DEFER_LATE 0
#define E2_AT 3
#define LAST_ORDER 1
#define AB_FENCE 1
#define GU_FENCE 2
#define XOUT_AT 19
#define XOUT_PACE 40
#define LAST_RED 1
#define NX 2
#define PFENCE 1
#define C_POLICY EVICT_FIRST
#define W_POLICY EVICT_NORMAL
constexpr int SPIN_LIMIT = 1 << 18;

__device__ uint4 g_ab[2 * S * D / 8];
__device__ uint4 g_h[S * F / 8];
__device__ uint2 g_stat[S];
__device__ uint4 g_cs[36 * 32];
__device__ unsigned g_cnt[17 * 32];
__device__ unsigned g_epoch[NCTA + NHELP];
#define PROF(role, i) do { } while (0)
#define PROFS(role, i) do { } while (0)
#define PROFCS(i) do { if ((threadIdx.x & 127) == 0) PROFS(threadIdx.x >> 7, i); } while (0)
#define PROFC(i) do { if ((threadIdx.x & 127) == 0) PROF(threadIdx.x >> 7, i); } while (0)

template <int V> struct Int { static constexpr int value = V; };
struct Maps {
  CUtensorMap cr, ci, h, hr, hi, wg, wu, wd, ab, x, out;
};
struct Ptrs {
  __nv_bfloat16* out;
  uint4 *ab, *h, *cs;
  uint2* stat;
  unsigned *cnt, *epoch;
  uint32_t zero;
};

__device__ __forceinline__ uint32_t smem_u32(const void* p) { return (uint32_t)__cvta_generic_to_shared(p); }
__device__ __forceinline__ void mbar_init(uint32_t bar, uint32_t cnt) {
  asm volatile("mbarrier.init.shared::cta.b64 [%0], %1;" :: "r"(bar), "r"(cnt));
}
__device__ __forceinline__ void mbar_expect_tx(uint32_t bar, uint32_t bytes) {
  asm volatile("mbarrier.arrive.expect_tx.shared::cta.b64 _, [%0], %1;" :: "r"(bar), "r"(bytes) : "memory");
}
__device__ __forceinline__ void mbar_arrive(uint32_t bar) {
  asm volatile("mbarrier.arrive.shared::cta.b64 _, [%0];" :: "r"(bar) : "memory");
}
__device__ __forceinline__ void mbar_arrive_cluster(uint32_t cluster_addr) {
  asm volatile("mbarrier.arrive.shared::cluster.b64 _, [%0];" :: "r"(cluster_addr) : "memory");
}
__device__ __forceinline__ uint32_t mapa(uint32_t addr, uint32_t cta) {
  uint32_t r; asm("mapa.shared::cluster.u32 %0, %1, %2;" : "=r"(r) : "r"(addr), "r"(cta)); return r;
}
__device__ __forceinline__ void mbar_wait(uint32_t bar, uint32_t parity) {
  asm volatile("{ .reg .pred p; .reg .u32 n;\n"
               "mbarrier.try_wait.parity.shared::cta.b64 p, [%0], %1;\n"
               "@p bra DONE;\n"
               "mov.u32 n, 0;\n"
               "LOOP:\n"
               "mbarrier.try_wait.parity.shared::cta.b64 p, [%0], %1;\n"
               "@p bra DONE;\n"
               "add.u32 n, n, 1;\n"
               "setp.lt.u32 p, n, %2;\n"
               "@p bra LOOP;\n"
               "DONE: }" :: "r"(bar), "r"(parity), "n"(SPIN_LIMIT) : "memory");
}
constexpr uint64_t EVICT_NORMAL = 0x1000000000000000ull, EVICT_FIRST = 0x12F0000000000000ull;
__device__ __forceinline__ void tma_2d(uint32_t dst, const CUtensorMap* m, int c0, int c1, uint32_t bar, uint64_t pol = EVICT_NORMAL) {
  asm volatile("cp.async.bulk.tensor.2d.shared::cluster.global.mbarrier::complete_tx::bytes.L2::cache_hint [%0], [%1, {%3, %4}], [%2], %5;"
               :: "r"(dst), "l"(m), "r"(bar), "r"(c0), "r"(c1), "l"(pol) : "memory");
}
__device__ __forceinline__ void tma_2d_mc(uint32_t dst, const CUtensorMap* m, int c0, int c1, uint32_t bar, uint64_t pol = EVICT_NORMAL) {
  asm volatile("cp.async.bulk.tensor.2d.shared::cluster.global.mbarrier::complete_tx::bytes.multicast::cluster.L2::cache_hint [%0], [%1, {%3, %4}], [%2], %5, %6;"
               :: "r"(dst), "l"(m), "r"(bar), "r"(c0), "r"(c1), "h"((uint16_t)3), "l"(pol) : "memory");
}
__device__ __forceinline__ void tma_atoms(uint32_t dst, const CUtensorMap* m, int c1, int c2, uint32_t bar) {
  asm volatile("cp.async.bulk.tensor.3d.shared::cluster.global.mbarrier::complete_tx::bytes [%0], [%1, {%5, %3, %4}], [%2];"
               :: "r"(dst), "l"(m), "r"(bar), "r"(c1), "r"(c2), "r"(0) : "memory");
}
__device__ __forceinline__ void tma_atoms_mc(uint32_t dst, const CUtensorMap* m, int c1, int c2, uint32_t bar) {
  asm volatile("cp.async.bulk.tensor.3d.shared::cluster.global.mbarrier::complete_tx::bytes.multicast::cluster [%0], [%1, {%5, %3, %4}], [%2], %6;"
               :: "r"(dst), "l"(m), "r"(bar), "r"(c1), "r"(c2), "r"(0), "h"((uint16_t)3) : "memory");
}
__device__ __forceinline__ void tma_5d_mc(uint32_t dst, const CUtensorMap* m, int c0, int c4, uint32_t bar, uint64_t pol = EVICT_NORMAL) {
  asm volatile("cp.async.bulk.tensor.5d.shared::cluster.global.mbarrier::complete_tx::bytes.multicast::cluster.L2::cache_hint [%0], [%1, {%3, %5, %5, %5, %4}], [%2], %6, %7;"
               :: "r"(dst), "l"(m), "r"(bar), "r"(c0), "r"(c4), "r"(0), "h"((uint16_t)3), "l"(pol) : "memory");
}
__device__ __forceinline__ void tma_store_2d(const CUtensorMap* m, uint32_t src, int c0, int c1) {
  asm volatile("cp.async.bulk.tensor.2d.global.shared::cta.bulk_group [%0, {%2, %3}], [%1];"
               :: "l"(m), "r"(src), "r"(c0), "r"(c1) : "memory");
}
__device__ __forceinline__ void tma_add_2d(const CUtensorMap* m, uint32_t src, int c0, int c1) {
  asm volatile("cp.reduce.async.bulk.tensor.2d.global.shared::cta.add.bulk_group [%0, {%2, %3}], [%1];"
               :: "l"(m), "r"(src), "r"(c0), "r"(c1) : "memory");
}
__device__ __forceinline__ void prefetch_2d(const CUtensorMap* m, int c0, int c1) {
  asm volatile("cp.async.bulk.prefetch.tensor.2d.L2.global [%0, {%1, %2}];" :: "l"(m), "r"(c0), "r"(c1) : "memory");
}
__device__ __forceinline__ void prefetch_5d(const CUtensorMap* m, int c0, int c4) {
  asm volatile("cp.async.bulk.prefetch.tensor.5d.L2.global [%0, {%1, %3, %3, %3, %2}];" :: "l"(m), "r"(c0), "r"(c4), "r"(0) : "memory");
}
__device__ __forceinline__ void prefetch_map(const CUtensorMap* m) {
  asm volatile("prefetch.tensormap [%0];" :: "l"(m) : "memory");
}
__device__ __forceinline__ unsigned ld_acquire(const unsigned* p) {
  unsigned v; asm volatile("ld.acquire.gpu.global.u32 %0, [%1];" : "=r"(v) : "l"(p) : "memory"); return v;
}
__device__ __forceinline__ bool elect_one() {
  uint32_t p; asm volatile("{ .reg .pred p; elect.sync _|p, 0xffffffff; selp.u32 %0, 1, 0, p; }" : "=r"(p)); return p != 0;
}
__device__ __forceinline__ uint4 lds128(uint32_t addr) {
  uint4 v; asm volatile("ld.shared.v4.u32 {%0,%1,%2,%3}, [%4];" : "=r"(v.x), "=r"(v.y), "=r"(v.z), "=r"(v.w) : "r"(addr) : "memory"); return v;
}
__device__ __forceinline__ uint32_t lds32(uint32_t addr) {
  uint32_t v; asm volatile("ld.volatile.shared.u32 %0, [%1];" : "=r"(v) : "r"(addr) : "memory"); return v;
}
__device__ __forceinline__ void ldsm4(uint32_t* d, uint32_t addr) {
  asm volatile("ldmatrix.sync.aligned.m8n8.x4.shared.b16 {%0,%1,%2,%3}, [%4];"
               : "=r"(d[0]), "=r"(d[1]), "=r"(d[2]), "=r"(d[3]) : "r"(addr) : "memory");
}
__device__ __forceinline__ void bar_sync(int id, int n) { asm volatile("bar.sync %0, %1;" :: "r"(id), "r"(n) : "memory"); }
__device__ __forceinline__ void bar_arrive(int id, int n) { asm volatile("bar.arrive %0, %1;" :: "r"(id), "r"(n) : "memory"); }

__device__ __forceinline__ uint64_t make_desc(uint32_t lo) {
  uint64_t d; asm("mov.b64 %0, {%1, %2};" : "=l"(d) : "r"(lo), "r"(0x40000040u)); return d;
}
__device__ __forceinline__ uint64_t make_desc64(uint32_t lo) {
  uint64_t d; asm("mov.b64 %0, {%1, %2};" : "=l"(d) : "r"(lo), "r"(0x80000020u)); return d;
}
constexpr uint32_t LBO_K = 1u << 16, LBO_N = (8192u >> 4) << 16, LBO_N64 = (4096u >> 4) << 16;
__device__ __forceinline__ void wgmma_fence() { asm volatile("wgmma.fence.sync.aligned;" ::: "memory"); }
__device__ __forceinline__ void wgmma_commit() { asm volatile("wgmma.commit_group.sync.aligned;" ::: "memory"); }
template <int N> __device__ __forceinline__ void wgmma_wait() { asm volatile("wgmma.wait_group.sync.aligned %0;" :: "n"(N) : "memory"); }

#define R8(a, b) "+f"(a[(b)+0]), "+f"(a[(b)+1]), "+f"(a[(b)+2]), "+f"(a[(b)+3]), "+f"(a[(b)+4]), "+f"(a[(b)+5]), "+f"(a[(b)+6]), "+f"(a[(b)+7])
#define R32(a, b) R8(a, b), R8(a, (b)+8), R8(a, (b)+16), R8(a, (b)+24)
#define W8(a, b) "=f"(a[(b)+0]), "=f"(a[(b)+1]), "=f"(a[(b)+2]), "=f"(a[(b)+3]), "=f"(a[(b)+4]), "=f"(a[(b)+5]), "=f"(a[(b)+6]), "=f"(a[(b)+7])
#define W32(a, b) W8(a, b), W8(a, (b)+8), W8(a, (b)+16), W8(a, (b)+24)
#define N256_REGS \
    "{%0,%1,%2,%3,%4,%5,%6,%7,%8,%9,%10,%11,%12,%13,%14,%15,%16,%17,%18,%19,%20,%21,%22,%23,%24,%25,%26,%27,%28,%29,%30,%31," \
    "%32,%33,%34,%35,%36,%37,%38,%39,%40,%41,%42,%43,%44,%45,%46,%47,%48,%49,%50,%51,%52,%53,%54,%55,%56,%57,%58,%59,%60,%61,%62,%63," \
    "%64,%65,%66,%67,%68,%69,%70,%71,%72,%73,%74,%75,%76,%77,%78,%79,%80,%81,%82,%83,%84,%85,%86,%87,%88,%89,%90,%91,%92,%93,%94,%95," \
    "%96,%97,%98,%99,%100,%101,%102,%103,%104,%105,%106,%107,%108,%109,%110,%111,%112,%113,%114,%115,%116,%117,%118,%119,%120,%121,%122,%123,%124,%125,%126,%127},"
template <int TB> __device__ __forceinline__ void wgmma_n256(float (&d)[128], uint64_t da, uint64_t db) {
  asm volatile("wgmma.mma_async.sync.aligned.m64n256k16.f32.bf16.bf16 " N256_REGS " %128, %129, 1, 1, 1, 0, %130;"
    : R32(d, 0), R32(d, 32), R32(d, 64), R32(d, 96) : "l"(da), "l"(db), "n"(TB));
}
template <int TB> __device__ __forceinline__ void wgmma_n256_first(float (&d)[128], uint64_t da, uint64_t db) {
  asm volatile("wgmma.mma_async.sync.aligned.m64n256k16.f32.bf16.bf16 " N256_REGS " %128, %129, 0, 1, 1, 0, %130;"
    : W32(d, 0), W32(d, 32), W32(d, 64), W32(d, 96) : "l"(da), "l"(db), "n"(TB));
}
template <bool DFT, bool FIRST> __device__ __forceinline__ void mma_step(float (&acc)[128], uint32_t da, uint32_t db) {
  wgmma_fence();
  if (FIRST) wgmma_n256_first<1>(acc, make_desc(da), make_desc64(db));
  #pragma unroll
  for (int kk = FIRST ? 1 : 0; kk < 4; kk++) {
    if (DFT) wgmma_n256<1>(acc, make_desc(da + kk * 2), make_desc64(db + kk * 64));
    else wgmma_n256<1>(acc, make_desc64(da + (kk & 1) * 2 + (kk >> 1) * 512), make_desc(db + kk * 128));
  }
  wgmma_commit();
}
#define N128_REGS \
    "{%0,%1,%2,%3,%4,%5,%6,%7,%8,%9,%10,%11,%12,%13,%14,%15,%16,%17,%18,%19,%20,%21,%22,%23,%24,%25,%26,%27,%28,%29,%30,%31," \
    "%32,%33,%34,%35,%36,%37,%38,%39,%40,%41,%42,%43,%44,%45,%46,%47,%48,%49,%50,%51,%52,%53,%54,%55,%56,%57,%58,%59,%60,%61,%62,%63},"
template <int TB, int OFF> __device__ __forceinline__ void wgmma_n128(float (&d)[128], uint64_t da, uint64_t db) {
  asm volatile("wgmma.mma_async.sync.aligned.m64n128k16.f32.bf16.bf16 " N128_REGS " %64, %65, 1, 1, 1, 0, %66;"
    : R32(d, OFF), R32(d, OFF + 32) : "l"(da), "l"(db), "n"(TB));
}
template <int TB, int OFF> __device__ __forceinline__ void wgmma_n128_first(float (&d)[128], uint64_t da, uint64_t db) {
  asm volatile("wgmma.mma_async.sync.aligned.m64n128k16.f32.bf16.bf16 " N128_REGS " %64, %65, 0, 1, 1, 0, %66;"
    : W32(d, OFF), W32(d, OFF + 32) : "l"(da), "l"(db), "n"(TB));
}
template <int TB, bool FIRST> __device__ __forceinline__ void mma_step128(float (&acc)[128], uint32_t da, uint32_t db) {
  wgmma_fence();
  if (FIRST) {
    wgmma_n128_first<TB, 0>(acc, make_desc(da), make_desc(db));
    wgmma_n128_first<TB, 64>(acc, make_desc(da + 512), make_desc(db));
  }
  #pragma unroll
  for (int kk = FIRST ? 1 : 0; kk < 4; kk++) {
    wgmma_n128<TB, 0>(acc, make_desc(da + kk * 2), make_desc(db + kk * (TB ? 128 : 2)));
    wgmma_n128<TB, 64>(acc, make_desc(da + 512 + kk * 2), make_desc(db + kk * (TB ? 128 : 2)));
  }
  wgmma_commit();
}
__device__ __forceinline__ void wgmma_n8_ta(float (&d)[4], uint64_t da, uint64_t db, int scale_d) {
  asm volatile("{ .reg .pred p; setp.ne.b32 p, %6, 0;\n"
    "wgmma.mma_async.sync.aligned.m64n8k16.f32.bf16.bf16 {%0,%1,%2,%3}, %4, %5, p, 1, 1, 1, 0; }"
    : "+f"(d[0]), "+f"(d[1]), "+f"(d[2]), "+f"(d[3]) : "l"(da), "l"(db), "r"(scale_d));
}
template <int OFF> __device__ __forceinline__ void wgmma_n64_rs(float (&d)[128], const uint32_t* a, uint64_t db) {
  asm volatile("wgmma.mma_async.sync.aligned.m64n64k16.f32.bf16.bf16 "
    "{%0,%1,%2,%3,%4,%5,%6,%7,%8,%9,%10,%11,%12,%13,%14,%15,%16,%17,%18,%19,%20,%21,%22,%23,%24,%25,%26,%27,%28,%29,%30,%31},"
    " {%32,%33,%34,%35}, %36, 1, 1, 1, 1;"
    : R32(d, OFF) : "r"(a[0]), "r"(a[1]), "r"(a[2]), "r"(a[3]), "l"(db));
}
template <int OFF> __device__ __forceinline__ void pin32(float (&d)[128]) { asm volatile("" : R32(d, OFF) :: "memory"); }
__device__ __forceinline__ void pin128(float (&d)[128]) { pin32<0>(d); pin32<32>(d); pin32<64>(d); pin32<96>(d); }

__device__ __forceinline__ uint32_t pack2(float lo, float hi) {
  uint32_t r; asm("cvt.rn.bf16x2.f32 %0, %1, %2;" : "=r"(r) : "f"(hi), "f"(lo)); return r;
}
__device__ __forceinline__ float bf_lo(uint32_t w) { return __uint_as_float(w << 16); }
__device__ __forceinline__ float bf_hi(uint32_t w) { return __uint_as_float(w & 0xffff0000u); }
__device__ __forceinline__ float geglu(float ag, float au, float k1, float k2, float k3) {
  const float z = ag * fmaf(ag * ag, k2, k1);
  float t; asm("tanh.approx.f32 %0, %1;" : "=f"(t) : "f"(z));
  const float w = (ag * au) * k3;
  return fmaf(w, t, w);
}
__device__ __forceinline__ uint4 ld_relaxed(const uint4* p) {
  uint4 v;
  asm volatile("ld.relaxed.gpu.global.v4.u32 {%0,%1,%2,%3}, [%4];"
               : "=r"(v.x), "=r"(v.y), "=r"(v.z), "=r"(v.w) : "l"(p) : "memory");
  return v;
}
__device__ __forceinline__ void st_relaxed(uint4* p, uint4 v) {
  asm volatile("st.relaxed.gpu.global.v4.u32 [%0], {%1,%2,%3,%4};"
               :: "l"(p), "r"(v.x), "r"(v.y), "r"(v.z), "r"(v.w) : "memory");
}

__device__ __forceinline__ void st_relaxed1(uint32_t* p, uint32_t a) {
  asm volatile("st.relaxed.gpu.global.u32 [%0], %1;" :: "l"(p), "r"(a) : "memory");
}
__device__ __forceinline__ void st_relaxed2(uint2* p, uint32_t a, uint32_t c) {
  asm volatile("st.relaxed.gpu.global.v2.u32 [%0], {%1,%2};" :: "l"(p), "r"(a), "r"(c) : "memory");
}

__device__ __forceinline__ constexpr uint32_t off_b(int u) { return u == 0 ? 0 : (6 + 2 * u) * SLOT; }
__device__ __forceinline__ constexpr uint32_t off_a(int u) { return (2 + u) * SLOT; }

__device__ __forceinline__ float sum8(const uint4& v) {
  return ((bf_lo(v.x) + bf_hi(v.x)) + (bf_lo(v.y) + bf_hi(v.y))) + ((bf_lo(v.z) + bf_hi(v.z)) + (bf_lo(v.w) + bf_hi(v.w)));
}
__device__ __forceinline__ float reduce8(float v) {
  v += __shfl_xor_sync(0xffffffffu, v, 1);
  v += __shfl_xor_sync(0xffffffffu, v, 2);
  return v + __shfl_xor_sync(0xffffffffu, v, 4);
}

__device__ __forceinline__ uint32_t tagged(float v, uint32_t tag) { return (__float_as_uint(v) & ~1u) | tag; }

__device__ __forceinline__ int cs_index(int p) { return (p & ~15) + ((p >> 1) & 3) * 4 + ((p >> 3) & 1) * 2 + (p & 1); }

template <int I> __device__ __forceinline__ void load_cs(float (&c)[32], uint32_t cs) {
  asm volatile("ld.shared.v4.f32 {%0,%1,%2,%3}, [%4];"
               : "=f"(c[4 * I]), "=f"(c[4 * I + 1]), "=f"(c[4 * I + 2]), "=f"(c[4 * I + 3]) : "r"(cs + I * 64));
}

template <int TB>
__device__ __forceinline__ void tile_mainloop(float (&acc)[128], uint32_t da0, uint32_t db0,
                                              uint32_t bars, int t, int ring_off, uint32_t rel, bool releaser,
                                              float (&mu)[4], float (&rs)[4], float (&c)[32], uint32_t stat, uint32_t cs) {
  int slot = (8 * t + ring_off) % 6, c6 = (8 * t) % 6, ps = 0;
  uint32_t par = ((8 * t) / 6) & 1;
  auto next_stage = [&]() {
    ps = slot;
    slot = slot == 5 ? 0 : slot + 1;
    if (++c6 == 6) { c6 = 0; par ^= 1; }
  };
  if (TB == 0) mbar_wait(bars + MB_X, 0);
  mbar_wait(bars + MB_RFULL + 8 * slot, par);
  PROFC(32 + 8 * t);
  mma_step128<TB, true>(acc, da0, db0 + (8 + slot) * (SLOT >> 4));
  next_stage();
  #pragma unroll 1
  for (int k = 1; k < 7; k++) {
    if (TB == 0) mbar_wait(bars + MB_X + 8 * k, 0);
    mbar_wait(bars + MB_RFULL + 8 * slot, par);
    PROFCS(32 + 8 * t + k);
    mma_step128<TB, false>(acc, da0 + k * (SLOT >> 4), db0 + (8 + slot) * (SLOT >> 4));
    const int done = ps;
    next_stage();
      wgmma_wait<1>();
    if (releaser) mbar_arrive_cluster(rel + 8 * done);
  }
  if (TB == 0) mbar_wait(bars + MB_X + 8 * 7, 0);
  mbar_wait(bars + MB_RFULL + 8 * slot, par);
  PROFCS(32 + 8 * t + 7);
  mma_step128<TB, false>(acc, da0 + 7 * (SLOT >> 4), db0 + (8 + slot) * (SLOT >> 4));
  bar_arrive(BAR_ORDER + ((t + 1) & 1), 256);
  wgmma_wait<1>();
  if (releaser) mbar_arrive_cluster(rel + 8 * ps);
  if (TB == 0) {
    wgmma_wait<0>();
    if (releaser) mbar_arrive_cluster(rel + 8 * slot);
  }
  mbar_wait(bars + MB_CS + 8 * t, 0);
  if (t < 2) {
    #pragma unroll
    for (int i = 0; i < 4; i++)
      asm volatile("ld.shared.v2.f32 {%0,%1}, [%2];" : "=f"(mu[i]), "=f"(rs[i]) : "r"(stat + ((i >> 1) * 64 + (i & 1) * 8) * 8));
  }
  load_cs<0>(c, cs);
  load_cs<1>(c, cs);
  if (TB != 0) { load_cs<4>(c, cs); load_cs<5>(c, cs); }
  wgmma_wait<0>();
  pin128(acc);
  if (TB != 0 && releaser) mbar_arrive_cluster(rel + 8 * slot);
}

__device__ __forceinline__ float link(float v, uint32_t prev, uint32_t zero) {
  return __uint_as_float(__float_as_uint(v) | (prev & zero));
}

__device__ __forceinline__ void sched_fence(uint32_t v, uint32_t zero) {
  asm volatile("{ .reg .pred p; setp.ne.u32 p, %0, 0; @p exit; }" :: "r"(v & zero) : "memory");
}

template <int G> __device__ __forceinline__ void ab_group(const float (&acc)[128], float (&c)[32], uint32_t cs, const float (&mu)[4],
                                                         const float (&rs)[4], float sign, uint4* dst, uint32_t zero, uint32_t prev = 0) {
  constexpr int m = G >> 2, rr = G & 3;
  if (m < 3 && rr < 2) load_cs<(2 * m + 2 + rr) & 7>(c, cs);
  const float sc = sign * rs[rr];
  uint32_t w[4];
  float mm = mu[rr];
  #pragma unroll
  for (int ii = 0; ii < 4; ii++) {
    const int i = 4 * m + ii, a = 64 * (rr >> 1) + 4 * i + 2 * (rr & 1);
    if (ii % AB_LINK == 0 && (ii > 0 || G % AB_FENCE != 0)) mm = link(mu[rr], ii > 0 ? w[ii > 0 ? ii - 1 : 0] : prev, zero);
    w[ii] = pack2(fmaf(-mm, c[2 * i], acc[a]) * sc, fmaf(-mm, c[2 * i + 1], acc[a + 1]) * sc);
  }
  dst[((rr >> 1) * 8 + (rr & 1)) * D + m * 32] = make_uint4(w[0], w[1], w[2], w[3]);
  if (G % AB_FENCE == AB_FENCE - 1) sched_fence(w[0], zero);
  if constexpr (G < 15) ab_group<G + 1>(acc, c, cs, mu, rs, sign, dst, zero, w[3]);
}
template <int G, int G1, bool LINKED>
__device__ __forceinline__ void gu_group(const float (&acc)[128], float (&c)[32], uint32_t cs, const float (&mu)[4],
                                         const float (&rs)[4], uint4* dst, uint32_t zero, uint32_t prev = 0) {
  constexpr int m = G >> 2, rr = G & 3;
  if (G == 1 || G == 2) { load_cs<(G + 1) & 7>(c, cs); load_cs<(G + 5) & 7>(c, cs); }
  const float k1 = 0.7978845608028654f * rs[rr], k3 = 0.5f * rs[rr] * rs[rr], k2 = 0.0713548162726002f * rs[rr] * k3;
  uint32_t w[4];
  #pragma unroll
  for (int ii = 0; ii < 4; ii++) {
    const int i = 4 * m + ii, a = 64 * (rr >> 1) + 4 * i + 2 * (rr & 1);
    const float mm = !LINKED ? mu[rr] : ii > 0 ? link(mu[rr], w[ii > 0 ? ii - 1 : 0], zero) : G % GU_FENCE != 0 ? link(mu[rr], prev, zero) : mu[rr];
    w[ii] = pack2(geglu(fmaf(-mm, c[2 * i], acc[a]), fmaf(-mm, c[16 + 2 * i], acc[a + 32]), k1, k2, k3),
                  geglu(fmaf(-mm, c[2 * i + 1], acc[a + 1]), fmaf(-mm, c[17 + 2 * i], acc[a + 33]), k1, k2, k3));
  }
  dst[((rr >> 1) * 8 + (rr & 1)) * F + m * 32] = make_uint4(w[0], w[1], w[2], w[3]);
  if (LINKED && G % GU_FENCE == GU_FENCE - 1) sched_fence(w[0], zero);
  if constexpr (G + 1 < G1) gu_group<G + 1, G1, LINKED>(acc, c, cs, mu, rs, dst, zero, w[3]);
}

__device__ __forceinline__ void gu_stash(float (&st)[16 * DEFER], const float (&acc)[128], const float (&c)[32], const float (&mu)[4]) {
  #pragma unroll
  for (int d = 0; d < DEFER; d++) {
    const int rr = 4 - DEFER + d;
    #pragma unroll
    for (int e = 0; e < 8; e++) {
      const int i = 4 + (e >> 1), a = 64 * (rr >> 1) + 4 * i + 2 * (rr & 1) + (e & 1);
      st[16 * d + e] = fmaf(-mu[rr], c[2 * i + (e & 1)], acc[a]);
      st[16 * d + 8 + e] = fmaf(-mu[rr], c[16 + 2 * i + (e & 1)], acc[a + 32]);
    }
  }
}
template <int DI> __device__ __forceinline__ void gu_deferred(const float (&st)[16 * DEFER], const float (&rs)[4], uint4* dst, uint32_t zero) {
  constexpr int rr = 4 - DEFER + DI;
  const float k1 = 0.7978845608028654f * rs[rr], k3 = 0.5f * rs[rr] * rs[rr], k2 = 0.0713548162726002f * rs[rr] * k3;
  uint32_t w[4];
  #pragma unroll
  for (int ii = 0; ii < 4; ii++) {
    float g0 = st[16 * DI + 2 * ii], g1 = st[16 * DI + 2 * ii + 1];
    if (ii > 0) { g0 = link(g0, w[ii > 0 ? ii - 1 : 0], zero); g1 = link(g1, w[ii > 0 ? ii - 1 : 0], zero); }
    w[ii] = pack2(geglu(g0, st[16 * DI + 8 + 2 * ii], k1, k2, k3), geglu(g1, st[16 * DI + 9 + 2 * ii], k1, k2, k3));
  }
  dst[((rr >> 1) * 8 + (rr & 1)) * F + 32] = make_uint4(w[0], w[1], w[2], w[3]);
}

__device__ __forceinline__ void row_stats(uint2* dst, uint32_t src, uint32_t bars) {
  mbar_wait(bars + MB_X, 0);
  const float piv = reduce8(sum8(lds128(src))) * (1.f / 64);
  float s1 = 0.f, s2 = 0.f;
  #pragma unroll 1
  for (int k = 0; k < 8; k++) {
    mbar_wait(bars + MB_X + 8 * k, 0);
    const uint4 v = lds128(src + k * SLOT);
    const uint32_t w[4] = {v.x, v.y, v.z, v.w};
    #pragma unroll
    for (int e = 0; e < 4; e++) {
      const float a = bf_lo(w[e]) - piv, c = bf_hi(w[e]) - piv;
      s1 += a + c;
      s2 = fmaf(c, c, fmaf(a, a, s2));
    }
  }
  s1 = reduce8(s1) * (1.f / D);
  s2 = reduce8(s2) * (1.f / D);
  const float rs = rsqrtf(fmaxf(s2 - s1 * s1, 0.f) + 1e-5f);
  mbar_wait(bars + MB_TAG, 0);
  const uint32_t tag = lds32(bars + SM_TAG);
  if ((threadIdx.x & 7) == 0) st_relaxed2(dst, tagged(piv + s1, tag), tagged(rs, tag));
}

template <int N> __device__ __forceinline__ void gather(const uint4* (&src)[N], const uint32_t (&dst)[N], uint32_t tag) {
  uint4 v[N];
  #pragma unroll 1
  for (int spins = 0; spins < SPIN_LIMIT; spins++) {
    uint32_t bad = 0;
    #pragma unroll
    for (int i = 0; i < N; i++) v[i] = ld_relaxed(src[i]);
    #pragma unroll
    for (int i = 0; i < N; i++) bad |= (v[i].x ^ tag) | (v[i].y ^ tag) | (v[i].z ^ tag) | (v[i].w ^ tag);
    if (__all_sync(0xffffffffu, (bad & 1) == 0)) break;
  }
  #pragma unroll
  for (int i = 0; i < N; i++)
    asm volatile("st.shared.v4.u32 [%0], {%1,%2,%3,%4};"
                 :: "r"(dst[i]), "r"(v[i].x & ~1u), "r"(v[i].y & ~1u), "r"(v[i].z & ~1u), "r"(v[i].w & ~1u) : "memory");
}

__device__ __forceinline__ void helper_cta(const Maps& maps, const Ptrs& ptrs, uint8_t* smem, int hb, int tid) {
  const uint32_t base = smem_u32(smem), bars = base + SMEM_BAR;
  auto tile_of = [&](int i) {
    const int j = i < 6 ? 2 * hb + (i & 1) : hb;
    return (j < 4 ? 4 * j : 3 * j + 4) + (i >> 1);
  };
  if (tid == 0)
    for (int u = 0; u < 12; u++) { mbar_init(bars + 8 * u, 1); mbar_init(bars + 96 + 8 * u, 2); }
  if (tid < 256) reinterpret_cast<uint32_t*>(smem + 12 * SLOT)[tid] = 0x3F803F80u;
  asm volatile("fence.proxy.async.shared::cta;" ::: "memory");
  __syncthreads();
  if (tid >= 256) {
    if (tid < 288 && elect_one()) {
      int u = 0;
      uint32_t par = 1;
      for (int i = 0; i < 7; i++) {
        const int col = tile_of(i) * 64;
        #pragma unroll 1
        for (int k = 0; k < 8; k++) {
          mbar_wait(bars + 96 + 8 * u, par);
          mbar_expect_tx(bars + 8 * u, SLOT);
          tma_2d(base + u * SLOT, &maps.wg, col, k * 64, bars + 8 * u);
          tma_2d(base + u * SLOT + 8192, &maps.wu, col, k * 64, bars + 8 * u);
          if (++u == 12) { u = 0; par ^= 1; }
        }
      }
    }
  } else {
    const unsigned epoch = ptrs.epoch[NCTA + hb] + 1;
    const int mat = __shfl_sync(0xffffffffu, tid >> 7, 0);
    const uint32_t d0 = (base & 0x3FFFF) >> 4;
    const int p = mat * 64 + ((tid >> 5) & 3) * 16 + ((tid & 31) >> 2);
    float acc[4];
    for (int i = 0; i < 7; i++) {
      #pragma unroll 1
      for (int k = 0; k < 8; k++) {
        const int s = i * 8 + k, u = s % 12;
        mbar_wait(bars + 8 * u, (s / 12) & 1);
        wgmma_fence();
        #pragma unroll
        for (int kk = 0; kk < 4; kk++)
          wgmma_n8_ta(acc, make_desc(d0 + LBO_N + u * (SLOT >> 4) + mat * 512 + kk * 128), make_desc(d0 + LBO_K + 12 * (SLOT >> 4)), (k | kk) != 0);
        wgmma_commit();
        wgmma_wait<0>();
        if ((tid & 127) == 0) mbar_arrive(bars + 96 + 8 * u);
      }
      asm volatile("" : "+f"(acc[0]), "+f"(acc[2]) :: "memory");
      if ((tid & 3) == 0) {
        uint32_t* dst = reinterpret_cast<uint32_t*>(ptrs.cs + (8 + tile_of(i)) * 32);
        st_relaxed1(dst + cs_index(p), tagged(acc[0], epoch & 1));
        st_relaxed1(dst + cs_index(p + 8), tagged(acc[2], epoch & 1));
      }
    }
    bar_sync(1, 256);
    if (tid == 0) ptrs.epoch[NCTA + hb] = epoch;
  }
}

template <int P> __device__ __forceinline__ void ship_quarter(const float (&acc)[128], const CUtensorMap* out, uint32_t stage,
                                                              int lane, int col, int row, __nv_bfloat16* optr) {
  #pragma unroll
  for (int i = 0; i < 4; i++)
    asm volatile("stmatrix.sync.aligned.m8n8.x4.shared.b16 [%0], {%1,%2,%3,%4};"
                 :: "r"(stage + (lane & 15) * 128 + (((2 * i + (lane >> 4)) ^ (lane & 7)) << 4)),
                    "r"(pack2(acc[32 * P + 8 * i], acc[32 * P + 8 * i + 1])), "r"(pack2(acc[32 * P + 8 * i + 2], acc[32 * P + 8 * i + 3])),
                    "r"(pack2(acc[32 * P + 8 * i + 4], acc[32 * P + 8 * i + 5])), "r"(pack2(acc[32 * P + 8 * i + 6], acc[32 * P + 8 * i + 7])) : "memory");
  if (P == 3 && LAST_RED) {
    __syncwarp();
    __nv_bfloat16* o = optr + (size_t)(row + (lane >> 3)) * D + col + (lane & 7) * 8;
    #pragma unroll
    for (int i = 0; i < 4; i++) {
      const uint4 v = lds128(stage + ((lane >> 3) + 4 * i) * 128 + (((lane & 7) ^ ((lane >> 3) + 4 * (i & 1))) << 4));
      asm volatile("red.global.add.noftz.v4.bf16x2 [%0], {%1,%2,%3,%4};" :: "l"(o + i * 4 * D), "r"(v.x), "r"(v.y), "r"(v.z), "r"(v.w) : "memory");
    }
    if (elect_one()) asm volatile("cp.async.bulk.wait_group.read 0;" ::: "memory");
    return;
  }
  asm volatile("fence.proxy.async.shared::cta;" ::: "memory");
  __syncwarp();
  if (elect_one()) {
    tma_add_2d(out, stage, col, row);
    asm volatile("cp.async.bulk.commit_group;" ::: "memory");
    if (P == 3) asm volatile("cp.async.bulk.wait_group.read 0;" ::: "memory");
  }
  __syncwarp();
}

template <int P> __device__ __forceinline__ void tail_mma(float (&acc)[128], const uint32_t (&af)[64], uint32_t db0, int st) {
  const uint32_t ob = P == 0 && st >= 2 ? 7 * SLOT + (st - 2) * 8192 : off_b((st + 1) & 3) + P * 8192;
  #pragma unroll
  for (int kk = 0; kk < 4; kk++) wgmma_n64_rs<32 * P>(acc, &af[16 * st + 4 * kk], make_desc(db0 + (ob >> 4) + kk * 128));
}
template <int P> __device__ __forceinline__ void tail_quarter(float (&acc)[128], const uint32_t (&af)[64], uint32_t db0) {
  wgmma_fence();
  #pragma unroll
  for (int st = 0; st < 4; st++) tail_mma<P>(acc, af, db0, st);
  wgmma_commit();
}
__device__ __forceinline__ void tail_load_a(uint32_t* af, uint32_t arow, int lane) {
  #pragma unroll
  for (int kk = 0; kk < 4; kk++)
    ldsm4(af + 4 * kk, arow + (kk >> 1) * 8192 + (((2 * (kk & 1) + (lane >> 4)) ^ ((lane >> 1) & 3)) << 4));
}

__global__ void __cluster_dims__(2, 1, 1) __launch_bounds__(NTHREADS, 1)
fused_kernel(const __grid_constant__ Ptrs ptrs, const __grid_constant__ Maps maps) {
  extern __shared__ __align__(1024) uint8_t smem_raw[];
  const uint32_t base = smem_u32(smem_raw);
  const uint32_t bars = base + SMEM_BAR;
  const int tid = threadIdx.x, lane = tid & 31;
  if (blockIdx.x >= NCTA) {
    helper_cta(maps, ptrs, smem_raw, blockIdx.x - NCTA, tid);
    return;
  }
  if (tid == 0) PROF(0, 0);
  const int wid = __shfl_sync(0xffffffffu, tid >> 5, 0), wg = wid >> 2;
  if (elect_one()) {
    if (wid < 11) {
      #pragma unroll
      for (int i = 0; i < 5; i++) mbar_init(bars + 40 * wid + 8 * i, wid < 2 ? 4 : (wid < 5 ? 2 : 1));
    } else {
      *reinterpret_cast<volatile uint32_t*>(smem_raw + SMEM_BAR + SM_PROG) = 0;
    }
    asm volatile("fence.mbarrier_init.release.cluster;" ::: "memory");
  }
  __syncwarp();
  asm volatile("barrier.cluster.arrive.relaxed.aligned;" ::: "memory");
  if (wid != 8) asm volatile("barrier.cluster.wait.aligned;" ::: "memory");

  int b;
  asm volatile("mov.u32 %0, %%ctaid.x;" : "=r"(b) :: "memory");
  const int rank = b & 1, cl = b >> 1;
  const int late = cl - 36, round7 = (late * 37) >> 8, pos7 = late - 7 * round7;
  const int rp = cl < 4 ? 1 : (cl < 36 ? (cl - 4) & 7 : pos7 + (pos7 >= 1));
  const int j = cl < 4 ? 4 + cl : (cl < 36 ? (cl - 4) >> 3 : 4 + round7);
  const int r = 2 * rp + rank;
  const int ring_off = j < 4 ? 2 : 4;
  const CUtensorMap* mh = (j & 4) ? &maps.hi : &maps.hr;
  auto load_x = [&](int k) {
    mbar_expect_tx(bars + MB_X + 8 * k, SLOT);
    tma_2d(base + k * SLOT, &maps.x, k * 64, r * 128, bars + MB_X + 8 * k);
  };
  auto load_h = [&](int k, int slot) {
    mbar_expect_tx(bars + MB_RFULL + 8 * slot, SLOT);
    tma_5d_mc(base + (8 + slot) * SLOT + rank * 8192, mh, k * 64, (j & 3) * 4 + rank * 2, bars + MB_RFULL + 8 * slot);
  };
  if (wid == 8) {
    if (elect_one()) {
      #pragma unroll
      for (int k = 0; k < NX; k++) load_x(k);
      PROF(2, 6);
    }
    __syncwarp();
    asm volatile("barrier.cluster.wait.aligned;" ::: "memory");
    if (elect_one()) {
      load_h(0, ring_off);
      #pragma unroll
      for (int k = NX; k < 2; k++) load_x(k);
      load_h(1, ring_off + 1);
      PROF(2, 7);
    }
    __syncwarp();
  }
  const int n = j & 1, kq = j >> 1;
  const int ntiles = j < 4 ? 5 : 4;
  const int gu0 = j < 4 ? 4 * j - 1 : 3 * j + 3;
  const int nd = j < 4 ? 14 : 18, d0 = j < 4 ? 14 * kq : 18 * kq - 8;
  const int nsteps1 = ntiles * 8, nsteps2 = nd + 7;

  if (wg == 2) {
    asm volatile("setmaxnreg.dec.sync.aligned.u32 40;");
    const int warp = wid & 3;
    const int c0 = n * 256 + ((kq + 1 + 2 * rank) & 3) * 64, c1 = n * 256 + ((kq + 2 + 2 * rank) & 3) * 64;
    if (warp == 0) {
      if (elect_one()) {
        volatile uint32_t* prog = reinterpret_cast<volatile uint32_t*>(smem_raw + SMEM_BAR + SM_PROG);
        int slot = j < 4 ? 4 : 0;
        #pragma unroll
        for (int s = 2; s < 8; s++) {
          if (s >= 6) {
            mbar_wait(bars + MB_HS + 8 * (s - 6), 0);
            mbar_wait(bars + MB_REMPTY + 8 * slot, 0);
          } else if (s >= NX) {
            load_x(s);
          }
          PROFS(2, 32 + s);
          load_h(s, slot);
          if (s == 5) { load_x(6); load_x(7); }
          slot = slot == 5 ? 0 : slot + 1;
        }
        const CUtensorMap* mw = rank ? &maps.wu : &maps.wg;
        int c6 = 2;
        uint32_t par = 0;
        #pragma unroll 1
        for (int s = 8; s < nsteps1; s++) {
          if (s < 14) mbar_wait(bars + MB_HS + 8 * (s - 6), 0);
          mbar_wait(bars + MB_REMPTY + 8 * slot, par);
          PROFS(2, 32 + s);
          mbar_expect_tx(bars + MB_RFULL + 8 * slot, SLOT);
          tma_2d_mc(base + (8 + slot) * SLOT + rank * 8192, mw, (gu0 + (s >> 3)) * 64, (s & 7) * 64, bars + MB_RFULL + 8 * slot, W_POLICY);
          *prog = s;
          slot = slot == 5 ? 0 : slot + 1;
          if (++c6 == 6) { c6 = 0; par ^= 1; }
        }
        PROF(2, 1);
        mbar_wait(bars + MB_AB, 0);
        if (PFENCE) asm volatile("fence.proxy.async.global;" ::: "memory");
        PROF(2, 2);
        #pragma unroll 1
        for (int t = 0; t < nd; t++) {
          const int u = t & 3, ds = d0 + t;
          if (t < 4) {
            const int last = t == 0 ? 0 : 2 * t - 1;
            mbar_wait(bars + MB_REMPTY + 8 * last, ((nsteps1 - 6 + last) / 6) & 1);
          } else {
            mbar_wait(bars + MB_EMPTY + 8 * u, ((t >> 2) - 1) & 1);
          }
          PROFS(2, 80 + t);
          const uint32_t full = bars + MB_FULL + 8 * u, sb = base + off_b(u) + rank * SLOT;
          mbar_expect_tx(full, 3 * SLOT);
          tma_2d(base + off_a(u), ds < 32 ? &maps.cr : &maps.ci, (ds & 31) * 64, r * 128, full, C_POLICY);
          tma_atoms_mc(sb, &maps.ab, ds * 8, c0 >> 5, full);
          tma_atoms_mc(sb + 8192, &maps.ab, ds * 8, c1 >> 5, full);
          *prog = nsteps1 + 2 * t;
        }
        PROF(2, 3);
        mbar_wait(bars + MB_H, 0);
        if (PFENCE) asm volatile("fence.proxy.async.global;" ::: "memory");
        PROF(2, 4);
        #pragma unroll 1
        for (int t = nd; t < nsteps2; t++) {
          const int u = t & 3, fs = kq * 7 + t - nd;
          mbar_wait(bars + MB_EMPTY + 8 * u, ((t >> 2) - 1) & 1);
          PROFS(2, 80 + t);
          const uint32_t full = bars + MB_FULL + 8 * u, sb = base + off_b(u) + rank * SLOT, sa = base + off_a(u);
          if (t < nsteps2 - 2) {
            mbar_expect_tx(full, 3 * SLOT);
            tma_atoms(sa, &maps.h, r * 16, fs * 2, full);
          } else {
            mbar_expect_tx(full, 3 * 8192);
          }
          if (t < nsteps2 - 2 || rank) tma_5d_mc(sb, &maps.wd, c0, fs * 2, full);
          tma_5d_mc(sb + 8192, &maps.wd, c1, fs * 2, full);
          if (t == nd) {
            mbar_expect_tx(bars + MB_EARLY, 2 * SLOT);
            tma_atoms(base + 6 * SLOT, &maps.h, r * 16, (kq * 7 + 6) * 2, bars + MB_EARLY);
            tma_5d_mc(base + 7 * SLOT + rank * 8192, &maps.wd, n * 256 + ((kq + 1) & 3) * 64, (kq * 7 + 5 + rank) * 2, bars + MB_EARLY);
          }
          if (t == nd + E2_AT) {
            mbar_wait(bars + MB_AREG, 0);
            mbar_wait(bars + MB_AREG + 8, 0);
            mbar_expect_tx(bars + MB_EARLY, SLOT);
            tma_atoms(base + 6 * SLOT, &maps.h, r * 16, (kq * 7 + 5) * 2, bars + MB_EARLY);
          }
        }
        PROF(2, 5);
        ptrs.epoch[b] += 1;
      }
    } else {
      if (warp == 1 && lane < 11) prefetch_map(&maps.cr + lane);
      if (warp == 1) {
        {
          const int p = r * 8 + (lane >> 2);
          const uint32_t hrow = base + 8 * SLOT + p * 128 + ((lane >> 2) & 1) * 64 + (lane & 3) * 16;
          const uint32_t done = mapa(bars + MB_HS, lane & 1);
          float hs = 0.f;
          int slot = ring_off;
          #pragma unroll 1
          for (int k = 0; k < 8; k++) {
            mbar_wait(bars + MB_RFULL + 8 * slot, k >= 6);
            hs += sum8(lds128(hrow + slot * SLOT)) + sum8(lds128((hrow ^ 64) + slot * SLOT));
            const float seen = __shfl_xor_sync(0xffffffffu, hs, 1);
            asm volatile("" :: "f"(seen) : "memory");
            if (lane < 2) mbar_arrive_cluster(done + 8 * k);
            slot = slot == 5 ? 0 : slot + 1;
          }
          hs += __shfl_xor_sync(0xffffffffu, hs, 1);
          hs += __shfl_xor_sync(0xffffffffu, hs, 2);
          mbar_wait(bars + MB_TAG, 0);
          if ((lane & 3) == 0) st_relaxed1(reinterpret_cast<uint32_t*>(ptrs.cs + j * 32) + cs_index(p), tagged(hs, lds32(bars + SM_TAG)));
          if (lane == 0) PROF(2, 13);
        }
        for (int t = 0; t < ntiles; t++) {
          bar_sync(BAR_PUB + t, 192);
          if (lane == 0) {
            asm volatile("red.release.gpu.global.add.u32 [%0], 1;" :: "l"(&ptrs.cnt[t == 0 ? 16 * 32 : r * 32]) : "memory");
            PROF(2, 15 + t);
          }
          __syncwarp();
        }
      } else if (warp == 2) {
        const uint32_t tag = (ptrs.epoch[b] + 1) & 1;
        if (lane == 0) {
          *reinterpret_cast<volatile uint32_t*>(smem_raw + SMEM_BAR + SM_TAG) = tag;
          mbar_arrive(bars + MB_TAG);
        }
        mbar_wait(bars + MB_X + 8 * 7, 0);
        const uint4* stat = reinterpret_cast<const uint4*>(ptrs.stat + r * 128) + lane;
        const uint4* src3[3] = {stat, stat + 32, ptrs.cs + j * 32 + lane};
        const uint32_t dst3[3] = {base + SMEM_STAT + lane * 16, base + SMEM_STAT + 512 + lane * 16, base + SMEM_CS + lane * 16};
        gather<3>(src3, dst3, tag);
        __syncwarp();
        if (lane == 0) { mbar_arrive(bars + MB_CS); PROF(2, 25); }
        for (int t = 1; t < ntiles + 2; t++) {
          if (t >= 2) bar_sync(BAR_PUB + t - 2, 192);
          if (t < ntiles) {
            const uint4* src[1] = {ptrs.cs + (8 + gu0 + t) * 32 + lane};
            const uint32_t dst[1] = {base + SMEM_CS + (t & 1) * 512 + lane * 16};
            gather<1>(src, dst, tag);
            __syncwarp();
            if (lane == 0) { mbar_arrive(bars + MB_CS + 8 * t); PROF(2, 25 + t); }
          }
        }
      } else if (elect_one()) {
        const unsigned epoch = ptrs.epoch[b] + 1;
        const volatile uint32_t* prog = reinterpret_cast<const volatile uint32_t*>(smem_raw + SMEM_BAR + SM_PROG);
        mbar_wait(bars + MB_X + 8 * j, 0);
        #pragma unroll 1
        for (int spins = 0; spins < SPIN_LIMIT && *prog < XOUT_AT; spins++) __nanosleep(100);
        #pragma unroll 1
        for (int i = 0; i < 8; i++) { tma_store_2d(&maps.out, base + j * SLOT + i * 2048, j * 64, r * 128 + i * 16); __nanosleep(XOUT_PACE); }
        asm volatile("cp.async.bulk.commit_group;" ::: "memory");
        asm volatile("cp.async.bulk.wait_group.read 0;" ::: "memory");
        mbar_arrive(bars + MB_XOUT);
        asm volatile("cp.async.bulk.wait_group 0;" ::: "memory");
        asm volatile("fence.proxy.async.global;" ::: "memory");
        asm volatile("red.release.gpu.global.add.u32 [%0], 1;" :: "l"(&ptrs.cnt[r * 32]) : "memory");
        int next = 0, stage = 0;
        #pragma unroll 1
        for (int spins = 0; spins < SPIN_LIMIT && (stage < 2 || next < nsteps2); spins++) {
          const int upto = ((int)*prog - nsteps1) / 2 + PF2_DIST;
          for (; next < nsteps2 && (next <= upto || upto >= nd - 1 + PF2_DIST); next++) {
            if (next < nd) {
              if ((next & 1) == n) prefetch_2d(d0 + next < 32 ? &maps.cr : &maps.ci, ((d0 + next) & 31) * 64, r * 128);
            } else if ((next & 7) == rp) {
              prefetch_5d(&maps.wd, c0, (kq * 7 + next - nd) * 2);
              prefetch_5d(&maps.wd, c1, (kq * 7 + next - nd) * 2);
            }
          }
          if (stage < 2) {
            const unsigned* cnt = &ptrs.cnt[stage == 0 ? 16 * 32 : r * 32];
            if ((int)(ld_acquire(cnt) - epoch * (stage == 0 ? 128 : 36)) >= 0) {
              if (!PFENCE) asm volatile("fence.proxy.async.global;" ::: "memory");
              mbar_arrive(bars + MB_AB + 8 * stage);
              PROF(2, 23 + stage);
              stage++;
            }
          }
          __nanosleep(stage < 2 ? 20 : 100);
        }
      }
    }
  } else {
    asm volatile("setmaxnreg.inc.sync.aligned.u32 232;");
    const uint32_t zero = ptrs.zero;
    const int warp = wid & 3, g = lane >> 2, q = lane & 3;
    const uint32_t peer_bars = mapa(bars, lane & 1);
    const bool releaser = (tid & 127) < 2;
    const uint32_t d_base = (base & 0x3FFFF) >> 4;
    const uint32_t db0 = d_base + LBO_N, da0 = d_base + wg * 512 + LBO_K;
    float acc[128], rs[4], stash[16 * DEFER];
    uint4* hdst;

    {
      const int t0 = (wg + ntiles) & 1;
      const int grp = r * 16 + warp * 2;
      const int chunk = g * 4 + (q ^ (g >> 1));
      if (t0 == 1) {
        const int lr = j * 16 + warp * 4 + (lane >> 3);
        row_stats(ptrs.stat + r * 128 + lr, base + lr * 128 + (lane & 7) * 16, bars);
      }
      PROFC(1);
      const uint32_t stat = base + SMEM_STAT + (warp * 16 + g) * 8, cs = base + SMEM_CS + t0 * 512 + q * 16;
      const uint32_t rel1 = peer_bars + MB_REMPTY;
      float mu[4], c[32];
      int t = t0;
      if (t0 == 0) {
        tile_mainloop<0>(acc, d_base + LBO_K, d_base + LBO_K, bars, 0, ring_off, rel1, releaser, mu, rs, c, stat, cs);
        PROFC(16);
        ab_group<0>(acc, c, cs, mu, rs, (j & 4) ? -1.f : 1.f,
                    ptrs.ab + ((j >> 2) * (S / 8) + grp) * D + (j & 3) * 128 + chunk, zero);
        bar_arrive(BAR_PUB, 192);
        PROFC(17);
        t = 2;
      }
      for (; t < ntiles; t += 2) {
        if (t == ntiles - 1) mbar_wait(bars + MB_XOUT, 0);
        bar_sync(BAR_ORDER + (t & 1), 256);
        tile_mainloop<1>(acc, d_base + LBO_K, db0, bars, t, ring_off, rel1, releaser, mu, rs, c, stat, cs);
        PROFC(16 + 2 * t);
        hdst = ptrs.h + grp * F + (gu0 + t) * 64 + chunk;
        gu_group<0, 4, true>(acc, c, cs, mu, rs, hdst, zero);
        if (t == ntiles - 1) {
          if constexpr (DEFER < 4) gu_group<4, 8 - DEFER, false>(acc, c, cs, mu, rs, hdst, zero);
          gu_stash(stash, acc, c, mu);
        } else {
          gu_group<4, 8, true>(acc, c, cs, mu, rs, hdst, zero);
          bar_arrive(BAR_PUB + t, 192);
        }
        PROFC(17 + 2 * t);
      }
    }

    if (wg == 0) bar_sync(BAR_ORDER + (ntiles & 1), 256);
    const uint32_t rel = peer_bars + MB_EMPTY;
    mbar_wait(bars + MB_FULL, 0);
    PROFC(80);
    mma_step<true, true>(acc, da0 + (off_a(0) >> 4), d_base + LBO_N64 + (off_b(0) >> 4));
    auto early_step = [&](auto idx) {
      constexpr int t = decltype(idx)::value;
      mbar_wait(bars + MB_FULL + 8 * (t & 3), (t >> 2) & 1);
      if (t == 4) PROFC(84); else PROFCS(80 + t);
      mma_step<true, false>(acc, da0 + (off_a(t & 3) >> 4), d_base + LBO_N64 + (off_b(t & 3) >> 4));
      if (DEFER_LATE) { wgmma_wait<1>(); if (releaser) mbar_arrive_cluster(rel + 8 * ((t - 1) & 3)); }
      if (wg == 1) {
        gu_deferred<t - 1>(stash, rs, hdst, zero);
        if (t == DEFER) bar_arrive(BAR_PUB + ntiles - 1, 192);
      }
      if (!DEFER_LATE) { wgmma_wait<1>(); if (releaser) mbar_arrive_cluster(rel + 8 * ((t - 1) & 3)); }
    };
    early_step(Int<1>());
    if constexpr (DEFER > 1) early_step(Int<2>());
    if constexpr (DEFER > 2) early_step(Int<3>());
    if constexpr (DEFER > 3) early_step(Int<4>());
    #pragma unroll 1
    for (int t = DEFER + 1; t < nd; t++) {
      const int u = t & 3;
      mbar_wait(bars + MB_FULL + 8 * u, (t >> 2) & 1);
      if (t == 4) PROFC(84); else PROFCS(80 + t);
      mma_step<true, false>(acc, da0 + (off_a(u) >> 4), d_base + LBO_N64 + (off_b(u) >> 4));
      wgmma_wait<1>();
      if (releaser) mbar_arrive_cluster(rel + 8 * ((t - 1) & 3));
    }
    const uint32_t par = ((nsteps2 - 4) >> 2) & 1;
    const uint32_t arow = base + (wg * 64 + warp * 16 + (lane & 15)) * 64;
    uint32_t af[64];
    mbar_wait(bars + MB_EARLY, 0);
    tail_load_a(af + 48, arow + 6 * SLOT, lane);
    #pragma unroll
    for (int i = 0; i < 3; i++) {
      const int u = (2 + i) & 3;
      if (LAST_ORDER && i == 2 && wg == 1) bar_sync(BAR_ORDER + 1, 256);
      mbar_wait(bars + MB_FULL + 8 * u, i < 2 ? par ^ 1 : par);
      PROFCS(80 + nd + i);
      mma_step<false, false>(acc, da0 - wg * 256 + (off_a(u) >> 4), db0 + (off_b(u) >> 4));
      if (LAST_ORDER && i == 2 && wg == 0) bar_arrive(BAR_ORDER + 1, 256);
      if (i == 0 && lane == 0) mbar_arrive(bars + MB_AREG + 8 * wg + ((af[48] | af[52] | af[56] | af[60]) & zero));
      wgmma_wait<1>();
      if (releaser) mbar_arrive_cluster(rel + 8 * ((u + 3) & 3));
    }
    mbar_wait(bars + MB_FULL + 8, par);
    tail_load_a(af, arow + off_a(1), lane);
    mbar_wait(bars + MB_FULL + 16, par);
    tail_load_a(af + 16, arow + off_a(2), lane);
    mbar_wait(bars + MB_EARLY, 1);
    tail_load_a(af + 32, arow + 6 * SLOT, lane);
    wgmma_wait<0>();
    pin128(acc);
    if (releaser) mbar_arrive_cluster(rel);
    PROFC(8);

    #pragma unroll
    for (int i = 0; i < 128; i++) { float v; asm volatile("mov.b32 %0, %1;" : "=f"(v) : "f"(acc[i])); acc[i] = v; }
    const uint32_t stage = base + (warp >> 1) * 8192 + wg * 4096 + (warp & 1) * 2048;
    const int orow = r * 128 + wg * 64 + warp * 16;
    if (wg == 1) bar_sync(BAR_TAIL, 256);
    tail_quarter<0>(acc, af, db0);
    if (wg == 0) bar_arrive(BAR_TAIL, 256);
    wgmma_wait<0>(); pin32<0>(acc);
    ship_quarter<0>(acc, &maps.out, stage + 6 * SLOT, lane, n * 256 + ((kq + 1) & 3) * 64, orow, ptrs.out);
    PROFC(9);
    mbar_wait(bars + MB_FULL + 24, par);
    wgmma_fence();
    #pragma unroll
    for (int st = 0; st < 3; st++) tail_mma<1>(acc, af, db0, st);
    wgmma_commit();
    mbar_wait(bars + MB_FULL, par ^ 1);
    wgmma_fence();
    tail_mma<1>(acc, af, db0, 3);
    wgmma_commit();
    wgmma_wait<0>(); pin32<32>(acc);
    ship_quarter<1>(acc, &maps.out, stage + 3 * SLOT, lane, n * 256 + ((kq + 2) & 3) * 64, orow, ptrs.out);
    PROFC(10);
    tail_quarter<2>(acc, af, db0);
    wgmma_wait<0>(); pin32<64>(acc);
    ship_quarter<2>(acc, &maps.out, stage + 4 * SLOT, lane, n * 256 + ((kq + 3) & 3) * 64, orow, ptrs.out);
    PROFC(11);
    tail_quarter<3>(acc, af, db0);
    wgmma_wait<0>(); pin32<96>(acc);
    PROFC(12);
    ship_quarter<3>(acc, &maps.out, stage + 5 * SLOT, lane, n * 256 + kq * 64, orow, ptrs.out);
    PROFC(13);
  }
}

typedef CUresult (*EncodeFn)(CUtensorMap*, CUtensorMapDataType, cuuint32_t, void*, const cuuint64_t*, const cuuint64_t*,
                             const cuuint32_t*, const cuuint32_t*, CUtensorMapInterleave, CUtensorMapSwizzle,
                             CUtensorMapL2promotion, CUtensorMapFloatOOBfill);

void encode(EncodeFn fn, CUtensorMap* m, const void* ptr, int rank, const cuuint64_t* dims, const cuuint64_t* strides,
            const cuuint32_t* box) {
  const cuuint32_t es[5] = {1, 1, 1, 1, 1};
  fn(m, CU_TENSOR_MAP_DATA_TYPE_BFLOAT16, rank, const_cast<void*>(ptr), dims, strides, box, es,
     CU_TENSOR_MAP_INTERLEAVE_NONE, CU_TENSOR_MAP_SWIZZLE_128B, CU_TENSOR_MAP_L2_PROMOTION_L2_128B,
     CU_TENSOR_MAP_FLOAT_OOB_FILL_NONE);
}
void map_2d(EncodeFn fn, CUtensorMap* m, const void* ptr, int cols, int rows, int box_rows) {
  const cuuint64_t dims[2] = {(cuuint64_t)cols, (cuuint64_t)rows}, strides[1] = {(cuuint64_t)cols * 2};
  const cuuint32_t box[2] = {64, (cuuint32_t)box_rows};
  encode(fn, m, ptr, 2, dims, strides, box);
}
void map_atoms(EncodeFn fn, CUtensorMap* m, const void* ptr, int cols, int rows, int box_groups) {
  const cuuint64_t dims[3] = {128, (cuuint64_t)rows / 8, (cuuint64_t)cols / 32}, strides[2] = {(cuuint64_t)cols * 16, 512};
  const cuuint32_t box[3] = {128, (cuuint32_t)box_groups, 2}, es[3] = {1, 1, 1};
  fn(m, CU_TENSOR_MAP_DATA_TYPE_UINT32, 3, const_cast<void*>(ptr), dims, strides, box, es, CU_TENSOR_MAP_INTERLEAVE_NONE,
     CU_TENSOR_MAP_SWIZZLE_NONE, CU_TENSOR_MAP_L2_PROMOTION_L2_128B, CU_TENSOR_MAP_FLOAT_OOB_FILL_NONE);
}
void map_perm(EncodeFn fn, CUtensorMap* m, const void* ptr, int rows, int box_groups) {
  const cuuint64_t dims[5] = {512, 2, 4, 4, (cuuint64_t)rows / 32}, strides[4] = {1024, 8 * 1024, 2 * 1024, 32 * 1024};
  const cuuint32_t box[5] = {64, 2, 4, 4, (cuuint32_t)box_groups};
  encode(fn, m, ptr, 5, dims, strides, box);
}

}

extern "C" void kernel_launch(void* const* d_in, const int* in_sizes, int n_in, void* d_out, int out_size) {
  void* fnp = nullptr;
  cudaDriverEntryPointQueryResult qr;
  cudaGetDriverEntryPoint("cuTensorMapEncodeTiled", &fnp, cudaEnableDefault, &qr);
  EncodeFn fn = (EncodeFn)fnp;
  void *p_ab, *p_h, *p_cs, *p_stat, *p_cnt, *p_epoch;
  cudaGetSymbolAddress(&p_ab, g_ab);
  cudaGetSymbolAddress(&p_h, g_h);
  cudaGetSymbolAddress(&p_cs, g_cs);
  cudaGetSymbolAddress(&p_stat, g_stat);
  cudaGetSymbolAddress(&p_cnt, g_cnt);
  cudaGetSymbolAddress(&p_epoch, g_epoch);
  Maps maps;
  map_2d(fn, &maps.cr, d_in[1], S, S, 128);
  map_2d(fn, &maps.ci, d_in[2], S, S, 128);
  map_atoms(fn, &maps.h, p_h, F, S, 16);
  map_perm(fn, &maps.hr, d_in[3], D, 2);
  map_perm(fn, &maps.hi, d_in[4], D, 2);
  map_2d(fn, &maps.wg, d_in[6], F, D, 64);
  map_2d(fn, &maps.wu, d_in[7], F, D, 64);
  map_perm(fn, &maps.wd, d_in[8], F, 2);
  map_atoms(fn, &maps.ab, p_ab, D, 2 * S, 8);
  map_2d(fn, &maps.x, d_in[0], D, S, 128);
  map_2d(fn, &maps.out, d_out, D, S, 16);
  const Ptrs ptrs = {(__nv_bfloat16*)d_out, (uint4*)p_ab, (uint4*)p_h, (uint4*)p_cs, (uint2*)p_stat,
                     (unsigned*)p_cnt, (unsigned*)p_epoch, 0u};
  cudaFuncSetAttribute(fused_kernel, cudaFuncAttributeMaxDynamicSharedMemorySize, SMEM_TOTAL);
  fused_kernel<<<NCTA + NHELP, NTHREADS, SMEM_TOTAL, cudaStreamPerThread>>>(ptrs, maps);
}
```
